```python
import torch

def _softmax(x, axis=-1):
    return torch.softmax(x, dim=axis)
def _gelu(x):
    return torch.nn.functional.gelu(x, approximate="tanh")
def _silu(x):
    return torch.nn.functional.silu(x)
def _sigmoid(x):
    return torch.sigmoid(x)
def _layernorm(x, axis=-1, eps=1e-5):
    m = x.mean(dim=axis, keepdim=True)
    v = x.var(dim=axis, keepdim=True, unbiased=False)
    return (x - m) / torch.sqrt(v + eps)
def _scatter_add(tgt, idx, src, axis=0):
    return tgt.clone().index_add_(axis, idx, src)
def _segment_sum(src, seg, n):
    out = torch.zeros((n,) + src.shape[1:], dtype=src.dtype)
    return out.index_add_(0, seg, src)
def _pad(x, pw):
    flat = tuple(v for pair in reversed(pw) for v in pair)
    return torch.nn.functional.pad(x, flat)

kernel_name = 'sequential_preLN__softmax_full_mha__glu_gated_bilinear__prompt'

def setup_inputs():

    _w = (lambda a: (lambda t: t.to(torch.bfloat16) if t.is_floating_point() else t)(torch.as_tensor(a)))
    def _A_setup():
        B, S, D = 1, 2048, 640
        return {
            "x": _w((lambda *s: torch.randn(*s, dtype=torch.bfloat16) * 0.05)(B, S, D)),
            "wqkv": _w((lambda *s: torch.randn(*s, dtype=torch.bfloat16) * 0.05)(D, 3 * D)),
            "wo": _w((lambda *s: torch.randn(*s, dtype=torch.bfloat16) * 0.05)(D, D)),
        }
    _A_in = _A_setup()

    def _B_setup():
        B, S, D, F = 1, 2048, 640, 1728
        return {
            "x": _w((lambda *s: torch.randn(*s, dtype=torch.bfloat16) * 0.05)(B, S, D)),
            "w_gate": _w((lambda *s: torch.randn(*s, dtype=torch.bfloat16) * 0.8)(D, F) * (D ** -0.5)),
            "w_up": _w((lambda *s: torch.randn(*s, dtype=torch.bfloat16) * 0.8)(D, F) * (D ** -0.5)),
            "w_down": _w((lambda *s: torch.randn(*s, dtype=torch.bfloat16) * 0.8)(F, D) * (F ** -0.5)),
        }
    _B_in = _B_setup()

    return {
        "A_x": _A_in["x"],
        "A_wqkv": _A_in["wqkv"],
        "A_wo": _A_in["wo"],
        "B_x": _B_in["x"],
        "B_w_gate": _B_in["w_gate"],
        "B_w_up": _B_in["w_up"],
        "B_w_down": _B_in["w_down"],
    }

def reference(A_x, A_wqkv, A_wo, B_x, B_w_gate, B_w_up, B_w_down):
    def _A_ref(x, wqkv, wo):
        B, S, D = x.shape
        H = 32; Dh = D // H
        qkv = (lambda x, *d: x.permute(*d))((x @ wqkv).reshape(B, S, 3, H, Dh), 2, 0, 3, 1, 4)
        q, k, v = qkv[0], qkv[1], qkv[2]
        scale = Dh ** -0.5
        scores = torch.einsum("bhqd,bhkd->bhqk", q, k) * scale
        p = _softmax(scores, axis=-1)
        o = torch.einsum("bhqk,bhkd->bhqd", p, v)
        return (lambda x, *d: x.permute(*d))(o, 0, 2, 1, 3).reshape(B, S, D) @ wo

    def _B_ref(x, w_gate, w_up, w_down):
        g = torch.einsum("bsd,df->bsf", x, w_gate)
        u = torch.einsum("bsd,df->bsf", x, w_up)
        h = g * u
        return torch.einsum("bsf,fd->bsd", h, w_down)

    x = A_x
    h = x + _A_ref(_layernorm(x, axis=-1), A_wqkv, A_wo)
    h2 = h + _B_ref(_layernorm(h, axis=-1), B_w_gate, B_w_up, B_w_down)
    return h2
```

```cpp
#include <cuda_runtime.h>
#include <cuda_bf16.h>
#include <cuda.h>
#include <stdint.h>

namespace {

constexpr int SEQ = 2048, DM = 640, NH = 32, HD = 20, FF = 1728, NQKV = 1920;
constexpr int IMG_HEAD = 98304;
constexpr int IMG_PART = NH * IMG_HEAD;
constexpr float LN_EPS = 1e-5f;
constexpr float QSCALE = 0.22360679774997896f * 1.4426950408889634f;
#define MUFU_BLOCKS 3

__device__ float2 g_st1[SEQ];
__device__ __align__(16) float g_cs1[2048];
__device__ __align__(1024) uint8_t g_img[3 * IMG_PART];
__device__ __align__(1024) __nv_bfloat16 g_o[SEQ * DM];
__device__ __align__(1024) __nv_bfloat16 g_h[SEQ * DM];
__device__ float2 g_st2[SEQ * 5];
__device__ __align__(16) float g_cs2[2 * FF];
__device__ __align__(1024) __nv_bfloat16 g_hh[SEQ * FF];
__device__ uint32_t g_consts[4] = {0u, 0u, 0x3F003F00u, 0x00010001u};

__device__ __forceinline__ uint32_t smem_u32(const void* p) { return (uint32_t)__cvta_generic_to_shared(p); }
__device__ __forceinline__ uint32_t opaque(uint32_t x) { uint32_t r; asm volatile("mov.u32 %0, %1;" : "=r"(r) : "r"(x)); return r; }
__device__ __forceinline__ void mbar_init(uint32_t bar, uint32_t cnt) { asm volatile("mbarrier.init.shared::cta.b64 [%0], %1;" :: "r"(bar), "r"(cnt) : "memory"); }
__device__ __forceinline__ void mbar_fence_init() { asm volatile("fence.mbarrier_init.release.cluster;" ::: "memory"); }
__device__ __forceinline__ void mbar_expect(uint32_t bar, uint32_t bytes) { asm volatile("mbarrier.arrive.expect_tx.shared::cta.b64 _, [%0], %1;" :: "r"(bar), "r"(bytes) : "memory"); }
__device__ __forceinline__ void mbar_arrive(uint32_t bar) { asm volatile("mbarrier.arrive.shared::cta.b64 _, [%0];" :: "r"(bar) : "memory"); }
__device__ __forceinline__ bool mbar_try(uint32_t bar, uint32_t parity) {
    uint32_t done;
    asm volatile("{\n.reg .pred p;\nmbarrier.try_wait.parity.shared::cta.b64 p, [%1], %2;\nselp.u32 %0, 1, 0, p;\n}\n" : "=r"(done) : "r"(bar), "r"(parity) : "memory");
    return done;
}
__device__ __forceinline__ void mbar_wait(uint32_t bar, uint32_t parity) {
    if (mbar_try(bar, parity)) return;
    uint32_t n = 0;
    while (!mbar_try(bar, parity)) { if (++n > (1u << 22)) __trap(); }
}
__device__ __forceinline__ bool elect_one() { uint32_t p; asm volatile("{\n.reg .pred P;\nelect.sync _|P, 0xffffffff;\nselp.u32 %0, 1, 0, P;\n}\n" : "=r"(p)); return p; }
__device__ __forceinline__ void bulk_g2s(uint32_t dst, const void* src, uint32_t bytes, uint32_t bar) {
    asm volatile("cp.async.bulk.shared::cluster.global.mbarrier::complete_tx::bytes [%0], [%1], %2, [%3];" :: "r"(dst), "l"(src), "r"(bytes), "r"(bar) : "memory");
}
__device__ __forceinline__ void tma_load(uint32_t dst, const CUtensorMap* tm, uint32_t bar, int c0, int c1) {
    asm volatile("cp.async.bulk.tensor.2d.shared::cluster.global.mbarrier::complete_tx::bytes [%0], [%1, {%3, %4}], [%2];"
        :: "r"(dst), "l"(tm), "r"(bar), "r"(c0), "r"(c1) : "memory");
}
__device__ __forceinline__ void tma_store(const CUtensorMap* tm, uint32_t src, int c0, int c1) {
    asm volatile("cp.async.bulk.tensor.2d.global.shared::cta.bulk_group [%0, {%2, %3}], [%1];" :: "l"(tm), "r"(src), "r"(c0), "r"(c1) : "memory");
}
__device__ __forceinline__ void tma_store_commit_wait() {
    asm volatile("cp.async.bulk.commit_group;" ::: "memory");
    asm volatile("cp.async.bulk.wait_group 0;" ::: "memory");
}
__device__ __forceinline__ void tmap_prefetch(const CUtensorMap* tm) { asm volatile("prefetch.tensormap [%0];" :: "l"(tm) : "memory"); }
__device__ __forceinline__ void l2_prefetch(const void* p, uint32_t bytes) { asm volatile("cp.async.bulk.prefetch.L2.global [%0], %1;" :: "l"(p), "r"(bytes) : "memory"); }
__device__ __forceinline__ void pdl_launch() { asm volatile("griddepcontrol.launch_dependents;" ::: "memory"); }
__device__ __forceinline__ void pdl_wait() { asm volatile("griddepcontrol.wait;" ::: "memory"); }
__device__ __forceinline__ void proxy_fence() { asm volatile("fence.proxy.async.shared::cta;" ::: "memory"); }
__device__ __forceinline__ void bar_sync(int id, int n) { asm volatile("bar.sync %0, %1;" :: "r"(id), "r"(n) : "memory"); }
__device__ __forceinline__ void bar_arrive(int id, int n) { asm volatile("bar.arrive %0, %1;" :: "r"(id), "r"(n) : "memory"); }
__device__ __forceinline__ void wg_fence() { asm volatile("wgmma.fence.sync.aligned;" ::: "memory"); }
__device__ __forceinline__ void wg_commit() { asm volatile("wgmma.commit_group.sync.aligned;" ::: "memory"); }
template<int N> __device__ __forceinline__ void wg_wait() { asm volatile("wgmma.wait_group.sync.aligned %0;" :: "n"(N) : "memory"); }
template<int N> __device__ __forceinline__ void pin(float (&d)[N]) {
    #pragma unroll
    for (int i = 0; i < N; i++) asm volatile("" : "+f"(d[i]) :: "memory");
}
__device__ __forceinline__ uint64_t mkdesc(uint32_t addr, uint32_t lbo, uint32_t sbo, uint32_t swz) {
    return (uint64_t)((addr & 0x3FFFF) >> 4) | ((uint64_t)(lbo >> 4) << 16) | ((uint64_t)(sbo >> 4) << 32) | ((uint64_t)swz << 62);
}
__device__ __forceinline__ uint32_t pack_bf16(float lo, float hi) { uint32_t r; asm("cvt.rn.bf16x2.f32 %0, %1, %2;" : "=r"(r) : "f"(hi), "f"(lo)); return r; }
__device__ __forceinline__ float ex2(float x) { float r; asm("ex2.approx.ftz.f32 %0, %1;" : "=f"(r) : "f"(x)); return r; }
__device__ __forceinline__ float bf_lo(uint32_t v) { return __uint_as_float(v << 16); }
__device__ __forceinline__ float bf_hi(uint32_t v) { return __uint_as_float(v & 0xFFFF0000u); }
__device__ __forceinline__ uint4 lds128(uint32_t a) { uint4 v; asm volatile("ld.shared.v4.u32 {%0,%1,%2,%3}, [%4];" : "=r"(v.x), "=r"(v.y), "=r"(v.z), "=r"(v.w) : "r"(a) : "memory"); return v; }
__device__ __forceinline__ void ldsm_x4_t(uint32_t a, uint32_t& r0, uint32_t& r1, uint32_t& r2, uint32_t& r3) {
    asm volatile("ldmatrix.sync.aligned.m8n8.x4.trans.shared.b16 {%0,%1,%2,%3}, [%4];" : "=r"(r0), "=r"(r1), "=r"(r2), "=r"(r3) : "r"(a) : "memory");
}
__device__ __forceinline__ void stsm_x4_t(uint32_t a, uint32_t r0, uint32_t r1, uint32_t r2, uint32_t r3) {
    asm volatile("stmatrix.sync.aligned.m8n8.x4.trans.shared.b16 [%0], {%1,%2,%3,%4};" :: "r"(a), "r"(r0), "r"(r1), "r"(r2), "r"(r3) : "memory");
}

__device__ __forceinline__ void wg_SS256_01(float (&d)[128], uint64_t da, uint64_t db, int sd) {
  asm volatile("{\n.reg .pred p;\nsetp.ne.b32 p, %130, 0;\n"
    "wgmma.mma_async.sync.aligned.m64n256k16.f32.bf16.bf16 {%0,%1,%2,%3,%4,%5,%6,%7,%8,%9,%10,%11,%12,%13,%14,%15,%16,%17,%18,%19,%20,%21,%22,%23,%24,%25,%26,%27,%28,%29,%30,%31,%32,%33,%34,%35,%36,%37,%38,%39,%40,%41,%42,%43,%44,%45,%46,%47,%48,%49,%50,%51,%52,%53,%54,%55,%56,%57,%58,%59,%60,%61,%62,%63,%64,%65,%66,%67,%68,%69,%70,%71,%72,%73,%74,%75,%76,%77,%78,%79,%80,%81,%82,%83,%84,%85,%86,%87,%88,%89,%90,%91,%92,%93,%94,%95,%96,%97,%98,%99,%100,%101,%102,%103,%104,%105,%106,%107,%108,%109,%110,%111,%112,%113,%114,%115,%116,%117,%118,%119,%120,%121,%122,%123,%124,%125,%126,%127}, %128, %129, p, 1, 1, 0, 1;\n}\n"
    : "+f"(d[0]),"+f"(d[1]),"+f"(d[2]),"+f"(d[3]),"+f"(d[4]),"+f"(d[5]),"+f"(d[6]),"+f"(d[7]),"+f"(d[8]),"+f"(d[9]),"+f"(d[10]),"+f"(d[11]),"+f"(d[12]),"+f"(d[13]),"+f"(d[14]),"+f"(d[15]),"+f"(d[16]),"+f"(d[17]),"+f"(d[18]),"+f"(d[19]),"+f"(d[20]),"+f"(d[21]),"+f"(d[22]),"+f"(d[23]),"+f"(d[24]),"+f"(d[25]),"+f"(d[26]),"+f"(d[27]),"+f"(d[28]),"+f"(d[29]),"+f"(d[30]),"+f"(d[31]),"+f"(d[32]),"+f"(d[33]),"+f"(d[34]),"+f"(d[35]),"+f"(d[36]),"+f"(d[37]),"+f"(d[38]),"+f"(d[39]),"+f"(d[40]),"+f"(d[41]),"+f"(d[42]),"+f"(d[43]),"+f"(d[44]),"+f"(d[45]),"+f"(d[46]),"+f"(d[47]),"+f"(d[48]),"+f"(d[49]),"+f"(d[50]),"+f"(d[51]),"+f"(d[52]),"+f"(d[53]),"+f"(d[54]),"+f"(d[55]),"+f"(d[56]),"+f"(d[57]),"+f"(d[58]),"+f"(d[59]),"+f"(d[60]),"+f"(d[61]),"+f"(d[62]),"+f"(d[63]),"+f"(d[64]),"+f"(d[65]),"+f"(d[66]),"+f"(d[67]),"+f"(d[68]),"+f"(d[69]),"+f"(d[70]),"+f"(d[71]),"+f"(d[72]),"+f"(d[73]),"+f"(d[74]),"+f"(d[75]),"+f"(d[76]),"+f"(d[77]),"+f"(d[78]),"+f"(d[79]),"+f"(d[80]),"+f"(d[81]),"+f"(d[82]),"+f"(d[83]),"+f"(d[84]),"+f"(d[85]),"+f"(d[86]),"+f"(d[87]),"+f"(d[88]),"+f"(d[89]),"+f"(d[90]),"+f"(d[91]),"+f"(d[92]),"+f"(d[93]),"+f"(d[94]),"+f"(d[95]),"+f"(d[96]),"+f"(d[97]),"+f"(d[98]),"+f"(d[99]),"+f"(d[100]),"+f"(d[101]),"+f"(d[102]),"+f"(d[103]),"+f"(d[104]),"+f"(d[105]),"+f"(d[106]),"+f"(d[107]),"+f"(d[108]),"+f"(d[109]),"+f"(d[110]),"+f"(d[111]),"+f"(d[112]),"+f"(d[113]),"+f"(d[114]),"+f"(d[115]),"+f"(d[116]),"+f"(d[117]),"+f"(d[118]),"+f"(d[119]),"+f"(d[120]),"+f"(d[121]),"+f"(d[122]),"+f"(d[123]),"+f"(d[124]),"+f"(d[125]),"+f"(d[126]),"+f"(d[127])
    : "l"(da), "l"(db), "r"(sd));
}
__device__ __forceinline__ void wg_SS128_01(float (&d)[64], uint64_t da, uint64_t db, int sd) {
  asm volatile("{\n.reg .pred p;\nsetp.ne.b32 p, %66, 0;\n"
    "wgmma.mma_async.sync.aligned.m64n128k16.f32.bf16.bf16 {%0,%1,%2,%3,%4,%5,%6,%7,%8,%9,%10,%11,%12,%13,%14,%15,%16,%17,%18,%19,%20,%21,%22,%23,%24,%25,%26,%27,%28,%29,%30,%31,%32,%33,%34,%35,%36,%37,%38,%39,%40,%41,%42,%43,%44,%45,%46,%47,%48,%49,%50,%51,%52,%53,%54,%55,%56,%57,%58,%59,%60,%61,%62,%63}, %64, %65, p, 1, 1, 0, 1;\n}\n"
    : "+f"(d[0]),"+f"(d[1]),"+f"(d[2]),"+f"(d[3]),"+f"(d[4]),"+f"(d[5]),"+f"(d[6]),"+f"(d[7]),"+f"(d[8]),"+f"(d[9]),"+f"(d[10]),"+f"(d[11]),"+f"(d[12]),"+f"(d[13]),"+f"(d[14]),"+f"(d[15]),"+f"(d[16]),"+f"(d[17]),"+f"(d[18]),"+f"(d[19]),"+f"(d[20]),"+f"(d[21]),"+f"(d[22]),"+f"(d[23]),"+f"(d[24]),"+f"(d[25]),"+f"(d[26]),"+f"(d[27]),"+f"(d[28]),"+f"(d[29]),"+f"(d[30]),"+f"(d[31]),"+f"(d[32]),"+f"(d[33]),"+f"(d[34]),"+f"(d[35]),"+f"(d[36]),"+f"(d[37]),"+f"(d[38]),"+f"(d[39]),"+f"(d[40]),"+f"(d[41]),"+f"(d[42]),"+f"(d[43]),"+f"(d[44]),"+f"(d[45]),"+f"(d[46]),"+f"(d[47]),"+f"(d[48]),"+f"(d[49]),"+f"(d[50]),"+f"(d[51]),"+f"(d[52]),"+f"(d[53]),"+f"(d[54]),"+f"(d[55]),"+f"(d[56]),"+f"(d[57]),"+f"(d[58]),"+f"(d[59]),"+f"(d[60]),"+f"(d[61]),"+f"(d[62]),"+f"(d[63])
    : "l"(da), "l"(db), "r"(sd));
}
__device__ __forceinline__ void wg_SS64_01(float (&d)[32], uint64_t da, uint64_t db, int sd) {
  asm volatile("{\n.reg .pred p;\nsetp.ne.b32 p, %34, 0;\n"
    "wgmma.mma_async.sync.aligned.m64n64k16.f32.bf16.bf16 {%0,%1,%2,%3,%4,%5,%6,%7,%8,%9,%10,%11,%12,%13,%14,%15,%16,%17,%18,%19,%20,%21,%22,%23,%24,%25,%26,%27,%28,%29,%30,%31}, %32, %33, p, 1, 1, 0, 1;\n}\n"
    : "+f"(d[0]),"+f"(d[1]),"+f"(d[2]),"+f"(d[3]),"+f"(d[4]),"+f"(d[5]),"+f"(d[6]),"+f"(d[7]),"+f"(d[8]),"+f"(d[9]),"+f"(d[10]),"+f"(d[11]),"+f"(d[12]),"+f"(d[13]),"+f"(d[14]),"+f"(d[15]),"+f"(d[16]),"+f"(d[17]),"+f"(d[18]),"+f"(d[19]),"+f"(d[20]),"+f"(d[21]),"+f"(d[22]),"+f"(d[23]),"+f"(d[24]),"+f"(d[25]),"+f"(d[26]),"+f"(d[27]),"+f"(d[28]),"+f"(d[29]),"+f"(d[30]),"+f"(d[31])
    : "l"(da), "l"(db), "r"(sd));
}
__device__ __forceinline__ void wg_SS80_10(float (&d)[40], uint64_t da, uint64_t db, int sd) {
  asm volatile("{\n.reg .pred p;\nsetp.ne.b32 p, %42, 0;\n"
    "wgmma.mma_async.sync.aligned.m64n80k16.f32.bf16.bf16 {%0,%1,%2,%3,%4,%5,%6,%7,%8,%9,%10,%11,%12,%13,%14,%15,%16,%17,%18,%19,%20,%21,%22,%23,%24,%25,%26,%27,%28,%29,%30,%31,%32,%33,%34,%35,%36,%37,%38,%39}, %40, %41, p, 1, 1, 1, 0;\n}\n"
    : "+f"(d[0]),"+f"(d[1]),"+f"(d[2]),"+f"(d[3]),"+f"(d[4]),"+f"(d[5]),"+f"(d[6]),"+f"(d[7]),"+f"(d[8]),"+f"(d[9]),"+f"(d[10]),"+f"(d[11]),"+f"(d[12]),"+f"(d[13]),"+f"(d[14]),"+f"(d[15]),"+f"(d[16]),"+f"(d[17]),"+f"(d[18]),"+f"(d[19]),"+f"(d[20]),"+f"(d[21]),"+f"(d[22]),"+f"(d[23]),"+f"(d[24]),"+f"(d[25]),"+f"(d[26]),"+f"(d[27]),"+f"(d[28]),"+f"(d[29]),"+f"(d[30]),"+f"(d[31]),"+f"(d[32]),"+f"(d[33]),"+f"(d[34]),"+f"(d[35]),"+f"(d[36]),"+f"(d[37]),"+f"(d[38]),"+f"(d[39])
    : "l"(da), "l"(db), "r"(sd));
}
__device__ __forceinline__ void wg_SS160_10(float (&d)[80], uint64_t da, uint64_t db, int sd) {
  asm volatile("{\n.reg .pred p;\nsetp.ne.b32 p, %82, 0;\n"
    "wgmma.mma_async.sync.aligned.m64n160k16.f32.bf16.bf16 {%0,%1,%2,%3,%4,%5,%6,%7,%8,%9,%10,%11,%12,%13,%14,%15,%16,%17,%18,%19,%20,%21,%22,%23,%24,%25,%26,%27,%28,%29,%30,%31,%32,%33,%34,%35,%36,%37,%38,%39,%40,%41,%42,%43,%44,%45,%46,%47,%48,%49,%50,%51,%52,%53,%54,%55,%56,%57,%58,%59,%60,%61,%62,%63,%64,%65,%66,%67,%68,%69,%70,%71,%72,%73,%74,%75,%76,%77,%78,%79}, %80, %81, p, 1, 1, 1, 0;\n}\n"
    : "+f"(d[0]),"+f"(d[1]),"+f"(d[2]),"+f"(d[3]),"+f"(d[4]),"+f"(d[5]),"+f"(d[6]),"+f"(d[7]),"+f"(d[8]),"+f"(d[9]),"+f"(d[10]),"+f"(d[11]),"+f"(d[12]),"+f"(d[13]),"+f"(d[14]),"+f"(d[15]),"+f"(d[16]),"+f"(d[17]),"+f"(d[18]),"+f"(d[19]),"+f"(d[20]),"+f"(d[21]),"+f"(d[22]),"+f"(d[23]),"+f"(d[24]),"+f"(d[25]),"+f"(d[26]),"+f"(d[27]),"+f"(d[28]),"+f"(d[29]),"+f"(d[30]),"+f"(d[31]),"+f"(d[32]),"+f"(d[33]),"+f"(d[34]),"+f"(d[35]),"+f"(d[36]),"+f"(d[37]),"+f"(d[38]),"+f"(d[39]),"+f"(d[40]),"+f"(d[41]),"+f"(d[42]),"+f"(d[43]),"+f"(d[44]),"+f"(d[45]),"+f"(d[46]),"+f"(d[47]),"+f"(d[48]),"+f"(d[49]),"+f"(d[50]),"+f"(d[51]),"+f"(d[52]),"+f"(d[53]),"+f"(d[54]),"+f"(d[55]),"+f"(d[56]),"+f"(d[57]),"+f"(d[58]),"+f"(d[59]),"+f"(d[60]),"+f"(d[61]),"+f"(d[62]),"+f"(d[63]),"+f"(d[64]),"+f"(d[65]),"+f"(d[66]),"+f"(d[67]),"+f"(d[68]),"+f"(d[69]),"+f"(d[70]),"+f"(d[71]),"+f"(d[72]),"+f"(d[73]),"+f"(d[74]),"+f"(d[75]),"+f"(d[76]),"+f"(d[77]),"+f"(d[78]),"+f"(d[79])
    : "l"(da), "l"(db), "r"(sd));
}
__device__ __forceinline__ void wg_RS128_00(float (&d)[64], uint32_t a0, uint32_t a1, uint32_t a2, uint32_t a3, uint64_t db, int sd) {
  asm volatile("{\n.reg .pred p;\nsetp.ne.b32 p, %69, 0;\n"
    "wgmma.mma_async.sync.aligned.m64n128k16.f32.bf16.bf16 {%0,%1,%2,%3,%4,%5,%6,%7,%8,%9,%10,%11,%12,%13,%14,%15,%16,%17,%18,%19,%20,%21,%22,%23,%24,%25,%26,%27,%28,%29,%30,%31,%32,%33,%34,%35,%36,%37,%38,%39,%40,%41,%42,%43,%44,%45,%46,%47,%48,%49,%50,%51,%52,%53,%54,%55,%56,%57,%58,%59,%60,%61,%62,%63}, {%64,%65,%66,%67}, %68, p, 1, 1, 0;\n}\n"
    : "+f"(d[0]),"+f"(d[1]),"+f"(d[2]),"+f"(d[3]),"+f"(d[4]),"+f"(d[5]),"+f"(d[6]),"+f"(d[7]),"+f"(d[8]),"+f"(d[9]),"+f"(d[10]),"+f"(d[11]),"+f"(d[12]),"+f"(d[13]),"+f"(d[14]),"+f"(d[15]),"+f"(d[16]),"+f"(d[17]),"+f"(d[18]),"+f"(d[19]),"+f"(d[20]),"+f"(d[21]),"+f"(d[22]),"+f"(d[23]),"+f"(d[24]),"+f"(d[25]),"+f"(d[26]),"+f"(d[27]),"+f"(d[28]),"+f"(d[29]),"+f"(d[30]),"+f"(d[31]),"+f"(d[32]),"+f"(d[33]),"+f"(d[34]),"+f"(d[35]),"+f"(d[36]),"+f"(d[37]),"+f"(d[38]),"+f"(d[39]),"+f"(d[40]),"+f"(d[41]),"+f"(d[42]),"+f"(d[43]),"+f"(d[44]),"+f"(d[45]),"+f"(d[46]),"+f"(d[47]),"+f"(d[48]),"+f"(d[49]),"+f"(d[50]),"+f"(d[51]),"+f"(d[52]),"+f"(d[53]),"+f"(d[54]),"+f"(d[55]),"+f"(d[56]),"+f"(d[57]),"+f"(d[58]),"+f"(d[59]),"+f"(d[60]),"+f"(d[61]),"+f"(d[62]),"+f"(d[63])
    : "r"(a0), "r"(a1), "r"(a2), "r"(a3), "l"(db), "r"(sd));
}
__device__ __forceinline__ void wg_RS24_01(float (&d)[12], uint32_t a0, uint32_t a1, uint32_t a2, uint32_t a3, uint64_t db, int sd) {
  asm volatile("{\n.reg .pred p;\nsetp.ne.b32 p, %17, 0;\n"
    "wgmma.mma_async.sync.aligned.m64n24k16.f32.bf16.bf16 {%0,%1,%2,%3,%4,%5,%6,%7,%8,%9,%10,%11}, {%12,%13,%14,%15}, %16, p, 1, 1, 1;\n}\n"
    : "+f"(d[0]),"+f"(d[1]),"+f"(d[2]),"+f"(d[3]),"+f"(d[4]),"+f"(d[5]),"+f"(d[6]),"+f"(d[7]),"+f"(d[8]),"+f"(d[9]),"+f"(d[10]),"+f"(d[11])
    : "r"(a0), "r"(a1), "r"(a2), "r"(a3), "l"(db), "r"(sd));
}

__global__ void __launch_bounds__(256) k0_prep(const __nv_bfloat16* __restrict__ x, const __nv_bfloat16* __restrict__ wqkv) {
    __shared__ float red[8][16];
    pdl_launch();
    const int tid = threadIdx.x, lane = tid & 31, warp = tid >> 5;
    uint2 xr[2][5];
    #pragma unroll
    for (int r = 0; r < 2; r++) {
        const uint2* p = (const uint2*)(x + (size_t)(blockIdx.x * 16 + warp * 2 + r) * DM) + lane;
        #pragma unroll
        for (int i = 0; i < 5; i++) xr[r][i] = __ldg(p + i * 32);
    }
    uint4 wr[5];
    const bool docs = blockIdx.x < NQKV / 16;
    if (docs) {
        const uint4* p = (const uint4*)(wqkv + (size_t)(tid >> 1) * NQKV + blockIdx.x * 16 + (tid & 1) * 8);
        #pragma unroll
        for (int i = 0; i < 5; i++) wr[i] = __ldg(p + (size_t)i * 128 * (NQKV / 8));
    }
    #pragma unroll
    for (int r = 0; r < 2; r++) {
        float v[20];
        #pragma unroll
        for (int i = 0; i < 5; i++) { v[i * 4] = bf_lo(xr[r][i].x); v[i * 4 + 1] = bf_hi(xr[r][i].x); v[i * 4 + 2] = bf_lo(xr[r][i].y); v[i * 4 + 3] = bf_hi(xr[r][i].y); }
        float s = 0.f;
        #pragma unroll
        for (int i = 0; i < 20; i++) s += v[i];
        #pragma unroll
        for (int o = 16; o; o >>= 1) s += __shfl_xor_sync(0xffffffff, s, o);
        const float mean = s * (1.f / DM);
        float q = 0.f;
        #pragma unroll
        for (int i = 0; i < 20; i++) { float d = v[i] - mean; q += d * d; }
        #pragma unroll
        for (int o = 16; o; o >>= 1) q += __shfl_xor_sync(0xffffffff, q, o);
        if (lane == 0) g_st1[blockIdx.x * 16 + warp * 2 + r] = make_float2(mean, rsqrtf(q * (1.f / DM) + LN_EPS));
    }
    if (docs) {
        float c[8];
        #pragma unroll
        for (int j = 0; j < 8; j++) c[j] = 0.f;
        #pragma unroll
        for (int i = 0; i < 5; i++) {
            c[0] += bf_lo(wr[i].x); c[1] += bf_hi(wr[i].x); c[2] += bf_lo(wr[i].y); c[3] += bf_hi(wr[i].y);
            c[4] += bf_lo(wr[i].z); c[5] += bf_hi(wr[i].z); c[6] += bf_lo(wr[i].w); c[7] += bf_hi(wr[i].w);
        }
        #pragma unroll
        for (int j = 0; j < 8; j++) {
            #pragma unroll
            for (int o = 2; o < 32; o <<= 1) c[j] += __shfl_xor_sync(0xffffffff, c[j], o);
        }
        if (lane < 2) {
            #pragma unroll
            for (int j = 0; j < 8; j++) red[warp][lane * 8 + j] = c[j];
        }
        __syncthreads();
        if (tid < 16) {
            float s = 0.f;
            #pragma unroll
            for (int w = 0; w < 8; w++) s += red[w][tid];
            g_cs1[blockIdx.x * 16 + tid] = s;
        }
    }
}

constexpr int K1_STAGE = 49152, K1_NST = 4;
constexpr int K1_SMEM = K1_NST * K1_STAGE + 2048 + 1024 + 256 + 128;

__global__ void __maxnreg__(168)
k1_qkv(const __grid_constant__ CUtensorMap tmX, const __grid_constant__ CUtensorMap tmW) {
    extern __shared__ __align__(1024) uint8_t smem[];
    const uint32_t sb = opaque(smem_u32(smem));
    const uint32_t sCs = sb + K1_NST * K1_STAGE, sSt = sCs + 1024, sTab = sSt + 1024 + 1024, sFull = sTab + 256, sEmpty = sFull + 64;
    const int tid = threadIdx.x, lane = tid & 31;
    const int warp = __shfl_sync(0xffffffff, tid >> 5, 0);
    const int mb = blockIdx.x >> 3, nt = blockIdx.x & 7;
    auto load_stage = [&](int kb) {
        const int st = kb & 3;
        const uint32_t base = sb + st * K1_STAGE, bar = sFull + st * 8;
        mbar_expect(bar, K1_STAGE);
        tma_load(base, &tmX, bar, kb * 64, mb * 128);
        #pragma unroll
        for (int i = 0; i < 4; i++) tma_load(base + 16384 + i * 8192, &tmW, bar, nt * 256 + i * 64, kb * 64);
    };
    if (warp == 0 && elect_one()) {
        for (int i = 0; i < K1_NST; i++) { mbar_init(sFull + i * 8, 1); mbar_init(sEmpty + i * 8, 2); }
        mbar_fence_init();
        load_stage(0); load_stage(1);
    }
    __syncthreads();
    pdl_launch();
    if (warp == 4 && elect_one()) { load_stage(2); load_stage(3); }
    {
        const int wg = warp >> 2;
        float acc[128];
        const uint64_t dA = mkdesc(sb + wg * 8192, 16, 1024, 1), dB = mkdesc(sb + 16384, 8192, 1024, 1);
        #pragma unroll 1
        for (int kb = 0; kb < 10; kb++) {
            const int st = kb & 3;
            mbar_wait(sFull + st * 8, (kb >> 2) & 1);
            wg_fence();
            const uint64_t so = (uint64_t)(st * (K1_STAGE >> 4));
            #pragma unroll
            for (int k = 0; k < 4; k++) wg_SS256_01(acc, dA + so + k * 2, dB + so + k * 128, k > 0 ? 1 : kb);
            wg_commit();
            wg_wait<1>();
            if (kb > 0 && kb < 7) {
                if ((tid & 127) == 0) mbar_arrive(sEmpty + ((kb - 1) & 3) * 8);
                if (warp == (kb & 1) * 4) {
                    mbar_wait(sEmpty + ((kb - 1) & 3) * 8, ((kb - 1) >> 2) & 1);
                    if (elect_one()) load_stage(kb + 3);
                    __syncwarp();
                }
            }
            if (kb == 7 && warp == 7) {
                #pragma unroll
                for (int e = lane; e < 64; e += 32) {
                    const int g = nt * 64 + e, part = g / 160, gh = g - part * 160, head = gh / 5, q5 = gh - head * 5;
                    uint32_t v = (uint32_t)part * IMG_PART + head * IMG_HEAD + (q5 >> 1) * 128 + (q5 & 1) * 8;
                    v |= (q5 == 4 ? 4u : 0u) | (uint32_t)part;
                    asm volatile("st.shared.u32 [%0], %1;" :: "r"(sTab + e * 4), "r"(v) : "memory");
                }
                pdl_wait();
                #pragma unroll
                for (int i = 0; i < 2; i++) {
                    const float4 c = __ldcg((const float4*)g_cs1 + nt * 64 + i * 32 + lane);
                    const float4 s = __ldcg((const float4*)g_st1 + mb * 64 + i * 32 + lane);
                    asm volatile("st.shared.v4.f32 [%0], {%1,%2,%3,%4};" :: "r"(sCs + (i * 32 + lane) * 16), "f"(c.x), "f"(c.y), "f"(c.z), "f"(c.w) : "memory");
                    asm volatile("st.shared.v4.f32 [%0], {%1,%2,%3,%4};" :: "r"(sSt + (i * 32 + lane) * 16), "f"(s.x), "f"(s.y), "f"(s.z), "f"(s.w) : "memory");
                }
            }
        }
        wg_wait<0>();
        pin(acc);
        __syncthreads();
        const int r0 = wg * 64 + (warp & 3) * 16 + (lane >> 2);
        float2 st0, st1;
        asm volatile("ld.shared.v2.f32 {%0,%1}, [%2];" : "=f"(st0.x), "=f"(st0.y) : "r"(sSt + r0 * 8));
        asm volatile("ld.shared.v2.f32 {%0,%1}, [%2];" : "=f"(st1.x), "=f"(st1.y) : "r"(sSt + r0 * 8 + 64));
        const bool odd = lane & 1;
        const int row = mb * 128 + r0 + (odd ? 8 : 0);
        uint8_t* const dst = g_img + (row >> 3) * 384 + (row & 7) * 16;
        const bool emu = ((row >> 3) & 7) >= MUFU_BLOCKS;
        const uint32_t kx0 = emu ? ((row & 1) ? 0x43F84780u : 0x42FE4780u) : 0x3F180000u, kx1 = emu ? 0x00003B80u : 0x0000BA5Fu;
        #pragma unroll
        for (int j = 0; j < 32; j++) {
            float2 cs;
            asm volatile("ld.shared.v2.f32 {%0,%1}, [%2];" : "=f"(cs.x), "=f"(cs.y) : "r"(sCs + j * 32 + (lane & 3) * 8));
            uint32_t ent;
            asm volatile("ld.shared.u32 %0, [%1];" : "=r"(ent) : "r"(sTab + j * 8 + (lane & 2) * 2));
            const float sc = (nt * 256 + j * 8 < DM) ? QSCALE : 1.f;
            const float a = st0.y * sc, b = st1.y * sc;
            const uint32_t p0 = pack_bf16((acc[j * 4] - st0.x * cs.x) * a, (acc[j * 4 + 1] - st0.x * cs.y) * a);
            const uint32_t p1 = pack_bf16((acc[j * 4 + 2] - st1.x * cs.x) * b, (acc[j * 4 + 3] - st1.x * cs.y) * b);
            const uint32_t rcv = __shfl_xor_sync(0xffffffff, odd ? p0 : p1, 1);
            const uint32_t w0 = odd ? rcv : p0, w1 = odd ? p1 : rcv;
            const uint32_t part = ent & 3;
            uint8_t* d = dst + (ent & ~7u);
            if (part != 3) {
                if (ent & 4) {
                    const uint32_t e0 = part == 0 ? 0x3F803F80u : part == 1 ? kx0 : 0x00003F80u;
                    const uint32_t e1 = part == 0 ? 0x00003F80u : part == 1 ? kx1 : 0u;
                    *(uint4*)d = make_uint4(w0, w1, e0, e1);
                } else {
                    *(uint2*)d = make_uint2(w0, w1);
                }
            }
        }
    }
}

__device__ __forceinline__ uint32_t exp2_pair(float t0, float t1, uint32_t cm, uint32_t ce) {
    uint32_t y, mh, e, r;
    asm("mad.lo.u32 %0, %1, 65536, %2;" : "=r"(y) : "r"(__float_as_uint(t1)), "r"(__float_as_uint(t0)));
    asm("lop3.b32 %0, %1, 0x007F007F, %2, 0xEA;" : "=r"(mh) : "r"(y), "r"(cm));
    asm("lop3.b32 %0, %1, 0xFF80FF80, %2, 0xEA;" : "=r"(e) : "r"(y), "r"(ce));
    asm("fma.rn.bf16x2 %0, %1, %2, %3;" : "=r"(r) : "r"(y), "r"(mh), "r"(e));
    return r;
}
constexpr int K2_SMEM = 2 * IMG_HEAD + 2 * 128 * 48 + 64 + 64;
constexpr float SAFE_S = 100.f;

__device__ __forceinline__ void attn_store(const float (&o)[12], int rt, int warp, int lane, int head) {
    const float l0 = __shfl_sync(0xffffffff, o[8], (lane & ~3) | 2), l1 = __shfl_sync(0xffffffff, o[10], (lane & ~3) | 2);
    const float r0 = 1.f / l0, r1 = 1.f / l1;
    const int row = rt * 64 + (warp & 3) * 16 + (lane >> 2);
    uint32_t* op = (uint32_t*)(g_o + (size_t)row * DM + head * HD) + (lane & 3);
    #pragma unroll
    for (int b = 0; b < 3; b++) {
        if (b < 2 || (lane & 3) < 2) {
            op[b * 4] = pack_bf16(o[b * 4] * r0, o[b * 4 + 1] * r0);
            op[b * 4 + 8 * DM / 2] = pack_bf16(o[b * 4 + 2] * r1, o[b * 4 + 3] * r1);
        }
    }
}

__device__ __forceinline__ void attn_fallback(int head, int qblk, int warp, int lane, uint64_t dK0, uint64_t dK1, uint64_t dV) {
    const int wg = warp >> 2;
    #pragma unroll 1
    for (int t = wg; t < 8; t += 3) {
        const int rt = qblk * 8 + t;
        const uint32_t* qp = (const uint32_t*)(g_img + (size_t)head * IMG_HEAD + (rt * 8 + (warp & 3) * 2) * 384) + lane;
        uint32_t q[8];
        #pragma unroll
        for (int c = 0; c < 3; c++) { q[c * 2] = __ldcg(qp + c * 32); q[c * 2 + 1] = __ldcg(qp + 96 + c * 32); }
        if ((lane & 3) >= 2) { q[4] = 0; q[5] = 0; }
        asm volatile("ld.volatile.global.u32 %0, [%1];" : "=r"(q[6]) : "l"(g_consts));
        asm volatile("ld.volatile.global.u32 %0, [%1];" : "=r"(q[7]) : "l"(g_consts + 1));
        float o[12], s[64];
        #pragma unroll
        for (int i = 0; i < 12; i++) o[i] = 0.f;
        pin(o);
        float m0 = -INFINITY, m1 = -INFINITY;
        #pragma unroll 1
        for (int j = 0; j < 16; j++) {
            wg_fence();
            wg_RS128_00(s, q[0], q[1], q[2], q[3], dK0 + j * 384, 0);
            wg_RS128_00(s, q[4], q[5], q[6], q[7], dK1 + j * 384, 1);
            wg_commit();
            wg_wait<0>();
            pin(s);
            float x0 = m0, x1 = m1;
            #pragma unroll
            for (int b = 0; b < 16; b++) { x0 = fmaxf(x0, fmaxf(s[b * 4], s[b * 4 + 1])); x1 = fmaxf(x1, fmaxf(s[b * 4 + 2], s[b * 4 + 3])); }
            x0 = fmaxf(x0, __shfl_xor_sync(0xffffffff, x0, 1)); x0 = fmaxf(x0, __shfl_xor_sync(0xffffffff, x0, 2));
            x1 = fmaxf(x1, __shfl_xor_sync(0xffffffff, x1, 1)); x1 = fmaxf(x1, __shfl_xor_sync(0xffffffff, x1, 2));
            const float c0 = ex2(m0 - x0), c1 = ex2(m1 - x1);
            m0 = x0; m1 = x1;
            #pragma unroll
            for (int b = 0; b < 3; b++) { o[b * 4] *= c0; o[b * 4 + 1] *= c0; o[b * 4 + 2] *= c1; o[b * 4 + 3] *= c1; }
            pin(o);
            uint32_t p[32];
            #pragma unroll
            for (int b = 0; b < 16; b++) {
                p[b * 2] = pack_bf16(ex2(s[b * 4] - m0), ex2(s[b * 4 + 1] - m0));
                p[b * 2 + 1] = pack_bf16(ex2(s[b * 4 + 2] - m1), ex2(s[b * 4 + 3] - m1));
            }
            wg_fence();
            #pragma unroll
            for (int kk = 0; kk < 8; kk++) wg_RS24_01(o, p[kk * 4], p[kk * 4 + 1], p[kk * 4 + 2], p[kk * 4 + 3], dV + j * 384 + kk * 48, 1);
            wg_commit();
            wg_wait<0>();
            pin(o);
        }
        attn_store(o, rt, warp, lane, head);
    }
}

__global__ void __launch_bounds__(384, 1)
k2_attn(const __nv_bfloat16* __restrict__ wo, const __nv_bfloat16* __restrict__ wg_, const __nv_bfloat16* __restrict__ wu, const __nv_bfloat16* __restrict__ wd) {
    extern __shared__ __align__(1024) uint8_t smem[];
    const uint32_t sb = opaque(smem_u32(smem));
    const int tid = threadIdx.x, lane = tid & 31;
    const int warp = __shfl_sync(0xffffffff, tid >> 5, 0);
    pdl_launch();
    if (blockIdx.x >= 128) {
        const int e = blockIdx.x - 128;
        const __nv_bfloat16* w = (e < 2 ? wg_ : wu);
        if (warp < 3) {
            const uint8_t* base = (const uint8_t*)(warp == 0 ? w + (size_t)(e & 1) * 320 * FF : warp == 1 ? wd + (size_t)e * 432 * DM : wo + (size_t)e * 160 * DM);
            const uint32_t total = warp == 0 ? 320 * FF * 2 : warp == 1 ? 432 * DM * 2 : 160 * DM * 2;
            for (uint32_t off = lane * 8192; off < total; off += 32 * 8192) l2_prefetch(base + off, min(8192u, total - off));
        }
        float* red = (float*)smem;
        const int cgp = tid % 108, rg = tid / 108;
        if (rg < 3) {
            float c[8];
            #pragma unroll
            for (int j = 0; j < 8; j++) c[j] = 0.f;
            const uint4* p = (const uint4*)(w + (e & 1) * 864 + cgp * 8);
            #pragma unroll 1
            for (int r0 = rg; r0 < DM; r0 += 48) {
                uint4 v[16];
                #pragma unroll
                for (int i = 0; i < 16; i++) { const int r = r0 + i * 3; v[i] = r < DM ? __ldg(p + (size_t)r * (FF / 8)) : make_uint4(0, 0, 0, 0); }
                #pragma unroll
                for (int i = 0; i < 16; i++) {
                    c[0] += bf_lo(v[i].x); c[1] += bf_hi(v[i].x); c[2] += bf_lo(v[i].y); c[3] += bf_hi(v[i].y);
                    c[4] += bf_lo(v[i].z); c[5] += bf_hi(v[i].z); c[6] += bf_lo(v[i].w); c[7] += bf_hi(v[i].w);
                }
            }
            #pragma unroll
            for (int j = 0; j < 8; j++) red[rg * 864 + cgp * 8 + j] = c[j];
        }
        __syncthreads();
        for (int i = tid; i < 864; i += 384) g_cs2[e * 864 + i] = red[i] + red[864 + i] + red[1728 + i];
        pdl_wait();
        return;
    }
    const uint32_t sK = sb, sV = sb + IMG_HEAD, sX = sb + 2 * IMG_HEAD, sBar = sX + 2 * 128 * 48, sRed = sBar + 64;
    const int wg = warp >> 2;
    const int head = blockIdx.x >> 2, qblk = blockIdx.x & 3;
    if (tid == 0) {
        for (int i = 0; i < 5; i++) mbar_init(sBar + i * 8, 2);
        mbar_fence_init();
        asm volatile("st.shared.v2.u32 [%0], {%1, %1};" :: "r"(sRed), "r"(0u) : "memory");
    }
    uint32_t cm, ce;
    asm volatile("ld.volatile.global.u32 %0, [%1];" : "=r"(cm) : "l"(g_consts + 2));
    asm volatile("ld.volatile.global.u32 %0, [%1];" : "=r"(ce) : "l"(g_consts + 3));
    __syncthreads();
    pdl_wait();
    if ((warp == 0 || warp == 4) && elect_one()) {
        const uint8_t* src = g_img + (warp == 0 ? IMG_PART : 2 * IMG_PART) + (size_t)head * IMG_HEAD;
        const uint32_t dst = warp == 0 ? sK : sV;
        #pragma unroll
        for (int i = 0; i < 5; i++) {
            const uint32_t off = (i == 0 ? 0 : (1 << (i - 1))) * 6144, bytes = (i == 0 ? 1 : (1 << (i - 1))) * 6144;
            mbar_expect(sBar + i * 8, bytes);
            bulk_g2s(dst + off, src + off, bytes, sBar + i * 8);
        }
    }
    const uint64_t dK0 = mkdesc(sK, 128, 384, 0), dK1 = mkdesc(sK + 256, 0, 384, 0), dV = mkdesc(sV, 384, 128, 0);
    const uint32_t* qbase = (const uint32_t*)(g_img + (size_t)head * IMG_HEAD + (qblk * 64 + (warp & 3) * 2) * 384) + lane;
    const int njobs = wg == 1 ? 4 : 3;
    uint32_t qn[6];
    #pragma unroll
    for (int c = 0; c < 3; c++) { qn[c * 2] = __ldcg(qbase + wg * 768 + c * 32); qn[c * 2 + 1] = __ldcg(qbase + wg * 768 + 96 + c * 32); }
    uint32_t qmax = 0, bad = 0;
    #pragma unroll 1
    for (int job = 0; job < njobs; job++) {
        const int t = job < 2 ? wg + 3 * job : (wg == 0 || (wg == 1 && job == 2)) ? 6 : 7;
        const int kt0 = job < 2 ? 0 : wg == 0 ? 0 : wg == 1 ? (job == 2 ? 11 : 0) : 6;
        const int nkt = job < 2 ? 16 : wg == 0 ? 11 : wg == 1 ? (job == 2 ? 5 : 6) : 10;
        uint32_t q[6], z0, z1;
        #pragma unroll
        for (int i = 0; i < 6; i++) q[i] = qn[i];
        asm volatile("ld.volatile.global.u32 %0, [%1];" : "=r"(z0) : "l"(g_consts));
        asm volatile("ld.volatile.global.u32 %0, [%1];" : "=r"(z1) : "l"(g_consts + 1));
        {
            const int jn = job + 1;
            const int tn = jn < 2 ? wg + 3 * jn : (wg == 0 || (wg == 1 && jn == 2)) ? 6 : 7;
            #pragma unroll
            for (int c = 0; c < 3; c++) { qn[c * 2] = __ldcg(qbase + tn * 768 + c * 32); qn[c * 2 + 1] = __ldcg(qbase + tn * 768 + 96 + c * 32); }
        }
        float o[12], s[64];
        uint32_t p[32];
        uint64_t k0 = dK0 + kt0 * 384, k1 = dK1 + kt0 * 384, dv = dV + kt0 * 384;
        auto qk = [&]() {
            wg_RS128_00(s, q[0], q[1], q[2], q[3], k0, 0);
            wg_RS128_00(s, q[4], q[5], z0, z1, k1, 1);
        };
        auto softmax_pv = [&](int accum) {
            wg_wait<0>();
            pin(s);
            #pragma unroll
            for (int b = 0; b < 16; b++) {
                if ((b & 7) < MUFU_BLOCKS) {
                    p[b * 2] = pack_bf16(ex2(s[b * 4]), ex2(s[b * 4 + 1]));
                    p[b * 2 + 1] = pack_bf16(ex2(s[b * 4 + 2]), ex2(s[b * 4 + 3]));
                } else {
                    p[b * 2] = exp2_pair(s[b * 4], s[b * 4 + 1], cm, ce);
                    p[b * 2 + 1] = exp2_pair(s[b * 4 + 2], s[b * 4 + 3], cm, ce);
                }
            }
            wg_fence();
            #pragma unroll
            for (int kk = 0; kk < 8; kk++) wg_RS24_01(o, p[kk * 4], p[kk * 4 + 1], p[kk * 4 + 2], p[kk * 4 + 3], dv + kk * 48, kk > 0 ? 1 : accum);
        };
        if (job == 0) mbar_wait(sBar, 0);
        wg_fence();
        qk();
        wg_commit();
        {
            float n0 = 0.f, n1 = 0.f;
            #pragma unroll
            for (int c = 0; c < 3; c++) {
                const bool use = c < 2 || (lane & 3) < 2;
                const float a = bf_lo(q[c * 2]), b = bf_hi(q[c * 2]), e = bf_lo(q[c * 2 + 1]), f = bf_hi(q[c * 2 + 1]);
                n0 += use ? a * a + b * b : 0.f; n1 += use ? e * e + f * f : 0.f;
            }
            n0 += __shfl_xor_sync(0xffffffff, n0, 1); n0 += __shfl_xor_sync(0xffffffff, n0, 2);
            n1 += __shfl_xor_sync(0xffffffff, n1, 1); n1 += __shfl_xor_sync(0xffffffff, n1, 2);
            qmax = max(qmax, max(__float_as_uint(n0) & 0x7FFFFFFFu, __float_as_uint(n1) & 0x7FFFFFFFu));
        }
        int accum = 0, left = nkt - 1, seg = 1;
        #pragma unroll 1
        do {
            int n = left;
            if (job == 0) { mbar_wait(sBar + 8 * seg, 0); n = 1 << (seg - 1); seg++; }
            left -= n;
            #pragma unroll 1
            do {
                softmax_pv(accum);
                k0 += 384; k1 += 384; dv += 384; accum = 1;
                qk();
                wg_commit();
            } while (--n);
        } while (left);
        softmax_pv(1);
        wg_commit();
        wg_wait<0>();
        float of[12];
        #pragma unroll
        for (int i = 0; i < 12; i++) asm volatile("mov.b32 %0, %1;" : "=f"(of[i]) : "f"(o[i]));
        if (job >= 2) {
            if (wg == 1) {
                const uint32_t a = sX + (job - 2) * 6144 + (tid & 127) * 16;
                #pragma unroll
                for (int i = 0; i < 3; i++)
                    asm volatile("st.shared.v4.f32 [%0], {%1,%2,%3,%4};" :: "r"(a + i * 2048), "f"(of[i * 4]), "f"(of[i * 4 + 1]), "f"(of[i * 4 + 2]), "f"(of[i * 4 + 3]) : "memory");
                bar_arrive(job - 1, 256);
                continue;
            }
            bar_sync(wg == 0 ? 1 : 2, 256);
            const uint32_t a = sX + (wg >> 1) * 6144 + (tid & 127) * 16;
            #pragma unroll
            for (int i = 0; i < 3; i++) {
                const uint4 v = lds128(a + i * 2048);
                of[i * 4] += __uint_as_float(v.x); of[i * 4 + 1] += __uint_as_float(v.y); of[i * 4 + 2] += __uint_as_float(v.z); of[i * 4 + 3] += __uint_as_float(v.w);
            }
        }
        #pragma unroll
        for (int i = 0; i < 12; i++) bad |= ((__float_as_uint(of[i]) & 0x7F800000u) == 0x7F800000u);
        attn_store(of, qblk * 8 + t, warp, lane, head);
    }
    uint32_t kmax = 0;
    for (int key = tid; key < SEQ; key += 384) {
        const uint32_t a = sK + (key >> 3) * 384 + (key & 7) * 16;
        const uint4 u = lds128(a), v = lds128(a + 128), w = lds128(a + 256);
        const uint32_t e[10] = {u.x, u.y, u.z, u.w, v.x, v.y, v.z, v.w, w.x, w.y};
        float n = 0.f;
        #pragma unroll
        for (int i = 0; i < 10; i++) { const float x = bf_lo(e[i]), y = bf_hi(e[i]); n = fmaf(x, x, n); n = fmaf(y, y, n); }
        kmax = max(kmax, __float_as_uint(n) & 0x7FFFFFFFu);
    }
    kmax = __reduce_max_sync(0xffffffff, kmax);
    qmax = __reduce_max_sync(0xffffffff, qmax);
    if (lane == 0) {
        asm volatile("red.shared.max.u32 [%0], %1;" :: "r"(sRed), "r"(kmax) : "memory");
        asm volatile("red.shared.max.u32 [%0], %1;" :: "r"(sRed + 4), "r"(qmax) : "memory");
    }
    bad = __syncthreads_or(bad);
    uint32_t km, qm;
    asm volatile("ld.shared.v2.u32 {%0,%1}, [%2];" : "=r"(km), "=r"(qm) : "r"(sRed) : "memory");
    if (bad || !(__uint_as_float(km) * __uint_as_float(qm) * 1.01f <= SAFE_S * SAFE_S)) attn_fallback(head, qblk, warp, lane, dK0, dK1, dV);
}

__device__ __forceinline__ void resid_add_store(const float* acc, uint32_t sTile, int warp, int lane) {
    #pragma unroll
    for (int b = 0; b < 10; b += 2) {
        const int t = (b + (lane >> 4)) * 8 + (lane & 7), chunk = (warp & 3) * 2 + ((lane >> 3) & 1);
        const uint32_t a = sTile + t * 128 + ((chunk ^ (t & 7)) << 4);
        uint32_t r0, r1, r2, r3;
        ldsm_x4_t(a, r0, r1, r2, r3);
        r0 = pack_bf16(acc[b * 4] + bf_lo(r0), acc[b * 4 + 1] + bf_hi(r0));
        r1 = pack_bf16(acc[b * 4 + 2] + bf_lo(r1), acc[b * 4 + 3] + bf_hi(r1));
        r2 = pack_bf16(acc[b * 4 + 4] + bf_lo(r2), acc[b * 4 + 5] + bf_hi(r2));
        r3 = pack_bf16(acc[b * 4 + 6] + bf_lo(r3), acc[b * 4 + 7] + bf_hi(r3));
        stsm_x4_t(a, r0, r1, r2, r3);
    }
}

constexpr int K3_NW = 6;
constexpr int K3_SMEM = K3_NW * 16384 + 10 * 10240 + 2 * 10240 + 256;

__global__ void __launch_bounds__(288, 1)
k3_wo(const __grid_constant__ CUtensorMap tmWo, const __grid_constant__ CUtensorMap tmO, const __grid_constant__ CUtensorMap tmXr, const __grid_constant__ CUtensorMap tmH) {
    extern __shared__ __align__(1024) uint8_t smem[];
    const uint32_t sb = opaque(smem_u32(smem));
    const uint32_t sW = sb, sO = sW + K3_NW * 16384, sR = sO + 10 * 10240, sFull = sR + 2 * 10240, sEmpty = sFull + 80, sRes = sEmpty + 32;
    const int tid = threadIdx.x, lane = tid & 31;
    const int warp = __shfl_sync(0xffffffff, tid >> 5, 0);
    const int cg = blockIdx.x % 5, tb = blockIdx.x / 5;
    if (tid == 0) {
        for (int i = 0; i < 10; i++) mbar_init(sFull + i * 8, 2);
        for (int i = 0; i < 4; i++) mbar_init(sEmpty + i * 8, 2);
        mbar_init(sRes, 1);
        mbar_fence_init();
        tmap_prefetch(&tmWo); tmap_prefetch(&tmO); tmap_prefetch(&tmXr); tmap_prefetch(&tmH);
    }
    __syncthreads();
    pdl_launch();
    if (warp == 8) {
        if (elect_one()) {
            #pragma unroll 1
            for (int kb = 0; kb < K3_NW; kb++) {
                mbar_expect(sFull + kb * 8, 16384);
                tma_load(sW + kb * 16384, &tmWo, sFull + kb * 8, cg * 128, kb * 64);
                tma_load(sW + kb * 16384 + 8192, &tmWo, sFull + kb * 8, cg * 128 + 64, kb * 64);
            }
            mbar_expect(sRes, 20480);
            tma_load(sR, &tmXr, sRes, cg * 128, tb * 80);
            tma_load(sR + 10240, &tmXr, sRes, cg * 128 + 64, tb * 80);
        }
        __syncwarp();
        pdl_wait();
        if (elect_one()) {
            #pragma unroll 1
            for (int kb = 0; kb < 10; kb++) {
                mbar_expect(sFull + kb * 8, 10240);
                tma_load(sO + kb * 10240, &tmO, sFull + kb * 8, kb * 64, tb * 80);
            }
        }
        __syncwarp();
        #pragma unroll 1
        for (int kb = K3_NW; kb < 10; kb++) {
            const int sl = kb - K3_NW;
            mbar_wait(sEmpty + sl * 8, 0);
            if (elect_one()) {
                mbar_expect(sFull + kb * 8, 16384);
                tma_load(sW + sl * 16384, &tmWo, sFull + kb * 8, cg * 128, kb * 64);
                tma_load(sW + sl * 16384 + 8192, &tmWo, sFull + kb * 8, cg * 128 + 64, kb * 64);
            }
            __syncwarp();
        }
    } else {
        const int wg = warp >> 2;
        float acc[40];
        const uint64_t dA = mkdesc(sW + wg * 8192, 8192, 1024, 1), dB = mkdesc(sO, 16, 1024, 1);
        #pragma unroll
        for (int kb = 0; kb < 10; kb++) {
            mbar_wait(sFull + kb * 8, 0);
            wg_fence();
            #pragma unroll
            for (int k = 0; k < 4; k++) wg_SS80_10(acc, dA + (kb % K3_NW) * 1024 + k * 128, dB + kb * 640 + k * 2, (kb | k) ? 1 : 0);
            wg_commit();
            if (kb >= 1 && kb <= 4) { wg_wait<1>(); if ((tid & 127) == 0) mbar_arrive(sEmpty + (kb - 1) * 8); }
        }
        wg_wait<0>();
        pin(acc);
        mbar_wait(sRes, 0);
        resid_add_store(acc, sR + wg * 10240, warp, lane);
        proxy_fence();
        bar_sync(1, 256);
        if (tid == 0) {
            tma_store(&tmH, sR, cg * 128, tb * 80);
            tma_store(&tmH, sR + 10240, cg * 128 + 64, tb * 80);
            tma_store_commit_wait();
        }
        if (tid >= 32 && tid < 192) {
            const int u = tid - 32, t = u >> 1;
            const uint32_t a = sR + (u & 1) * 10240 + t * 128;
            float v[64];
            #pragma unroll
            for (int c = 0; c < 8; c++) {
                const uint4 w = lds128(a + ((c ^ (t & 7)) << 4));
                v[c * 8] = bf_lo(w.x); v[c * 8 + 1] = bf_hi(w.x); v[c * 8 + 2] = bf_lo(w.y); v[c * 8 + 3] = bf_hi(w.y);
                v[c * 8 + 4] = bf_lo(w.z); v[c * 8 + 5] = bf_hi(w.z); v[c * 8 + 6] = bf_lo(w.w); v[c * 8 + 7] = bf_hi(w.w);
            }
            float s0 = 0.f, s1 = 0.f, s2 = 0.f, s3 = 0.f;
            #pragma unroll
            for (int i = 0; i < 64; i += 4) { s0 += v[i]; s1 += v[i + 1]; s2 += v[i + 2]; s3 += v[i + 3]; }
            float s = (s0 + s1) + (s2 + s3);
            s += __shfl_xor_sync(0xffffffff, s, 1);
            const float mean = s * (1.f / 128.f);
            s0 = s1 = s2 = s3 = 0.f;
            #pragma unroll
            for (int i = 0; i < 64; i += 4) {
                const float d0 = v[i] - mean, d1 = v[i + 1] - mean, d2 = v[i + 2] - mean, d3 = v[i + 3] - mean;
                s0 = fmaf(d0, d0, s0); s1 = fmaf(d1, d1, s1); s2 = fmaf(d2, d2, s2); s3 = fmaf(d3, d3, s3);
            }
            float q = (s0 + s1) + (s2 + s3);
            q += __shfl_xor_sync(0xffffffff, q, 1);
            const int row = tb * 80 + t;
            if (!(u & 1) && row < SEQ) g_st2[row * 5 + cg] = make_float2(s, q);
        }
    }
}

constexpr int K4_NST = 4;
constexpr int K4_SMEM = 10 * 16384 + K4_NST * 16384 + 256;

template<int NB>
__device__ __forceinline__ void glu_store(const float (&a0)[NB * 8], const float (&a1)[NB * 8], int col0, int row, const float (&mean)[4], const float (&rs)[4], int lane) {
    #pragma unroll
    for (int g4 = 0; g4 < NB; g4 += 4) {
        uint32_t p[4][4];
        #pragma unroll
        for (int jj = 0; jj < 4; jj++) {
            const int j = g4 + jj;
            const float2 cgv = __ldg((const float2*)(g_cs2 + col0 + j * 8) + (lane & 3)), cuv = __ldg((const float2*)(g_cs2 + FF + col0 + j * 8) + (lane & 3));
            #pragma unroll
            for (int h = 0; h < 4; h++) {
                const float* g = (h < 2 ? a0 : a1) + j * 4 + (h & 1) * 2;
                const float* u = g + NB * 4;
                p[h][jj] = pack_bf16(((g[0] - mean[h] * cgv.x) * rs[h]) * ((u[0] - mean[h] * cuv.x) * rs[h]),
                                     ((g[1] - mean[h] * cgv.y) * rs[h]) * ((u[1] - mean[h] * cuv.y) * rs[h]));
            }
        }
        #pragma unroll
        for (int h = 0; h < 4; h++) {
            uint32_t* r = p[h];
            #pragma unroll
            for (int s = 1; s <= 2; s <<= 1) {
                #pragma unroll
                for (int i = 0; i < 4; i++) {
                    if (i & s) continue;
                    const bool up = lane & s;
                    const uint32_t rcv = __shfl_xor_sync(0xffffffff, up ? r[i] : r[i + s], s);
                    if (up) r[i] = rcv; else r[i + s] = rcv;
                }
            }
            *(uint4*)(g_hh + (size_t)(row + (h >> 1) * 64 + (h & 1) * 8) * FF + col0 + (g4 + (lane & 3)) * 8) = make_uint4(r[0], r[1], r[2], r[3]);
        }
    }
}

__global__ void __launch_bounds__(384, 1)
k4_glu(const __grid_constant__ CUtensorMap tmH, const __grid_constant__ CUtensorMap tmG64, const __grid_constant__ CUtensorMap tmU64,
       const __grid_constant__ CUtensorMap tmG32, const __grid_constant__ CUtensorMap tmU32) {
    extern __shared__ __align__(1024) uint8_t smem[];
    const uint32_t sb = opaque(smem_u32(smem));
    const uint32_t sA = sb, sB = sb + 10 * 16384, sAf = sB + K4_NST * 16384, sFull = sAf + 80, sEmpty = sFull + 32;
    const int tid = threadIdx.x, lane = tid & 31;
    const int warp = __shfl_sync(0xffffffff, tid >> 5, 0);
    const int mb = blockIdx.x >> 3, fs = blockIdx.x & 7;
    const int nfull = fs == 7 ? 2 : 3;
    const int full0 = fs * 224 + ((fs & 1) ? 32 : 0), half0 = fs * 224 + ((fs & 1) ? 0 : 192);
    if (tid == 0) {
        for (int i = 0; i < 10; i++) mbar_init(sAf + i * 8, 1);
        for (int i = 0; i < K4_NST; i++) { mbar_init(sFull + i * 8, 1); mbar_init(sEmpty + i * 8, 1); }
        mbar_fence_init();
        tmap_prefetch(&tmH); tmap_prefetch(&tmG64); tmap_prefetch(&tmU64); tmap_prefetch(&tmG32); tmap_prefetch(&tmU32);
    }
    __syncthreads();
    pdl_launch();
    if (warp >= 8) {
        asm volatile("setmaxnreg.dec.sync.aligned.u32 40;");
        if (warp > 8) return;
        const int nsteps = (nfull + 1) * 10;
        int unit = 0, kb = 0;
        #pragma unroll 1
        for (int s = 0; s < nsteps; s++) {
            const int st = s & 3;
            if (s == K4_NST) {
                pdl_wait();
                if (elect_one()) {
                    #pragma unroll 1
                    for (int i = 0; i < 10; i++) { mbar_expect(sAf + i * 8, 16384); tma_load(sA + i * 16384, &tmH, sAf + i * 8, i * 64, mb * 128); }
                }
                __syncwarp();
            }
            if (s >= K4_NST) mbar_wait(sEmpty + st * 8, ((s >> 2) & 1) ^ 1);
            if (elect_one()) {
                const uint32_t base = sB + st * 16384, bar = sFull + st * 8;
                if (unit < nfull) {
                    mbar_expect(bar, 16384);
                    tma_load(base, &tmG64, bar, full0 + unit * 64, kb * 64);
                    tma_load(base + 8192, &tmU64, bar, full0 + unit * 64, kb * 64);
                } else {
                    mbar_expect(bar, 8192);
                    tma_load(base, &tmG32, bar, half0, kb * 64);
                    tma_load(base + 4096, &tmU32, bar, half0, kb * 64);
                }
            }
            __syncwarp();
            if (++kb == 10) { kb = 0; unit++; }
        }
    } else {
        asm volatile("setmaxnreg.inc.sync.aligned.u32 232;");
        const int wg = warp >> 2;
        pdl_wait();
        float mean[4], rs[4];
        const int rbase = mb * 128 + (warp & 3) * 16 + (lane >> 2);
        #pragma unroll
        for (int i = 0; i < 4; i++) {
            const float2* sp = g_st2 + (rbase + (i >> 1) * 64 + (i & 1) * 8) * 5;
            float2 v[5];
            #pragma unroll
            for (int c = 0; c < 5; c++) v[c] = __ldcg(sp + c);
            const float m = (v[0].x + v[1].x + v[2].x + v[3].x + v[4].x) * (1.f / DM);
            float q = 0.f;
            #pragma unroll
            for (int c = 0; c < 5; c++) { const float d = v[c].x * (1.f / 128.f) - m; q += v[c].y + 128.f * d * d; }
            mean[i] = m; rs[i] = rsqrtf(q * (1.f / DM) + LN_EPS);
        }
        const uint64_t dA = mkdesc(sA, 16, 1024, 1), dB = mkdesc(sB, 8192, 1024, 1), dBh = mkdesc(sB, 4096, 512, 2);
        #pragma unroll 1
        for (int unit = wg; unit <= nfull; unit += 2) {
            const int s0 = unit * 10;
            if (unit > 0) bar_sync(1 + wg, 256);
            if (unit < nfull) {
                float a0[64], a1[64];
                #pragma unroll 1
                for (int kb = 0; kb < 10; kb++) {
                    const int s = s0 + kb, st = s & 3;
                    if (unit < 2) mbar_wait(sAf + kb * 8, 0);
                    mbar_wait(sFull + st * 8, (s >> 2) & 1);
                    if (kb == 9) bar_arrive(2 - wg, 256);
                    wg_fence();
                    const uint64_t da = dA + (uint64_t)(kb * 1024), db = dB + (uint64_t)(st * 1024);
                    #pragma unroll
                    for (int k = 0; k < 4; k++) {
                        wg_SS128_01(a0, da + k * 2, db + k * 128, k > 0 ? 1 : kb);
                        wg_SS128_01(a1, da + 512 + k * 2, db + k * 128, k > 0 ? 1 : kb);
                    }
                    wg_commit();
                    wg_wait<1>();
                    if (kb > 0 && (tid & 127) == 0) mbar_arrive(sEmpty + ((s - 1) & 3) * 8);
                }
                wg_wait<0>();
                pin(a0); pin(a1);
                if ((tid & 127) == 0) mbar_arrive(sEmpty + ((s0 + 9) & 3) * 8);
                glu_store<8>(a0, a1, full0 + unit * 64, rbase, mean, rs, lane);
            } else {
                float a0[32], a1[32];
                #pragma unroll 1
                for (int kb = 0; kb < 10; kb++) {
                    const int s = s0 + kb, st = s & 3;
                    mbar_wait(sFull + st * 8, (s >> 2) & 1);
                    wg_fence();
                    const uint64_t da = dA + (uint64_t)(kb * 1024), db = dBh + (uint64_t)(st * 1024);
                    #pragma unroll
                    for (int k = 0; k < 4; k++) {
                        wg_SS64_01(a0, da + k * 2, db + k * 64, k > 0 ? 1 : kb);
                        wg_SS64_01(a1, da + 512 + k * 2, db + k * 64, k > 0 ? 1 : kb);
                    }
                    wg_commit();
                    wg_wait<1>();
                    if (kb > 0 && (tid & 127) == 0) mbar_arrive(sEmpty + ((s - 1) & 3) * 8);
                }
                wg_wait<0>();
                pin(a0); pin(a1);
                glu_store<4>(a0, a1, half0, rbase, mean, rs, lane);
            }
        }
    }
}

constexpr int K5_STAGE = 16384 + 20480, K5_NST = 4;
constexpr int K5_SMEM = K5_NST * K5_STAGE + 40960 + 2 * 10240 + 256;

__global__ void __cluster_dims__(2, 1, 1) __launch_bounds__(288, 1)
k5_down(const __grid_constant__ CUtensorMap tmWd, const __grid_constant__ CUtensorMap tmHH, const __grid_constant__ CUtensorMap tmHr, const __grid_constant__ CUtensorMap tmOut) {
    extern __shared__ __align__(1024) uint8_t smem[];
    const uint32_t sb = opaque(smem_u32(smem));
    const uint32_t sX = sb + K5_NST * K5_STAGE, sR = sX + 40960, sFull = sR + 2 * 10240, sEmpty = sFull + 32, sRes = sEmpty + 32;
    const int tid = threadIdx.x, lane = tid & 31;
    const int warp = __shfl_sync(0xffffffff, tid >> 5, 0);
    const int rank = blockIdx.x & 1, pr = blockIdx.x >> 1, cg = pr % 5, tb = pr / 5;
    const int kb0 = rank ? 14 : 0, nkb = rank ? 13 : 14;
    if (tid == 0) {
        for (int i = 0; i < K5_NST; i++) { mbar_init(sFull + i * 8, 2); mbar_init(sEmpty + i * 8, 2); }
        mbar_init(sRes, 1);
        mbar_fence_init();
        tmap_prefetch(&tmWd); tmap_prefetch(&tmHH); tmap_prefetch(&tmHr); tmap_prefetch(&tmOut);
    }
    __syncthreads();
    asm volatile("barrier.cluster.arrive.relaxed.aligned;" ::: "memory");
    if (warp == 8) {
        if (elect_one()) {
            #pragma unroll 1
            for (int s = 0; s < K5_NST; s++) {
                mbar_expect(sFull + s * 8, 16384);
                tma_load(sb + s * K5_STAGE, &tmWd, sFull + s * 8, cg * 128, (kb0 + s) * 64);
                tma_load(sb + s * K5_STAGE + 8192, &tmWd, sFull + s * 8, cg * 128 + 64, (kb0 + s) * 64);
            }
        }
        __syncwarp();
        pdl_wait();
        #pragma unroll 1
        for (int s = 0; s < nkb; s++) {
            const int st = s & 3;
            if (s >= K5_NST) mbar_wait(sEmpty + st * 8, ((s >> 2) & 1) ^ 1);
            if (elect_one()) {
                const uint32_t base = sb + st * K5_STAGE, bar = sFull + st * 8;
                mbar_expect(bar, 20480);
                tma_load(base + 16384, &tmHH, bar, (kb0 + s) * 64, tb * 160);
                if (s >= K5_NST) {
                    mbar_expect(bar, 16384);
                    tma_load(base, &tmWd, bar, cg * 128, (kb0 + s) * 64);
                    tma_load(base + 8192, &tmWd, bar, cg * 128 + 64, (kb0 + s) * 64);
                }
                if (s == K5_NST - 1) {
                    mbar_expect(sRes, 20480);
                    tma_load(sR, &tmHr, sRes, cg * 128, tb * 160 + rank * 80);
                    tma_load(sR + 10240, &tmHr, sRes, cg * 128 + 64, tb * 160 + rank * 80);
                }
            }
            __syncwarp();
        }
        asm volatile("barrier.cluster.wait.aligned;" ::: "memory");
        asm volatile("barrier.cluster.arrive.relaxed.aligned;" ::: "memory");
        asm volatile("barrier.cluster.wait.aligned;" ::: "memory");
    } else {
        const int wg = warp >> 2;
        float acc[80];
        const uint64_t dA = mkdesc(sb + wg * 8192, 8192, 1024, 1), dB = mkdesc(sb + 16384, 16, 1024, 1);
        #pragma unroll 1
        for (int s = 0; s < nkb; s++) {
            const int st = s & 3;
            mbar_wait(sFull + st * 8, (s >> 2) & 1);
            wg_fence();
            const uint64_t so = (uint64_t)(st * (K5_STAGE >> 4));
            #pragma unroll
            for (int k = 0; k < 4; k++) wg_SS160_10(acc, dA + so + k * 128, dB + so + k * 2, k > 0 ? 1 : s);
            wg_commit();
            wg_wait<1>();
            if (s > 0 && (tid & 127) == 0) mbar_arrive(sEmpty + ((s - 1) & 3) * 8);
        }
        wg_wait<0>();
        pin(acc);
        asm volatile("barrier.cluster.wait.aligned;" ::: "memory");
        uint32_t remote;
        asm volatile("mapa.shared::cluster.u32 %0, %1, %2;" : "=r"(remote) : "r"(sX + tid * 16), "r"(rank ^ 1));
        float keep[40];
        #pragma unroll
        for (int i = 0; i < 10; i++) {
            float v[4];
            #pragma unroll
            for (int c = 0; c < 4; c++) { v[c] = rank ? acc[i * 4 + c] : acc[40 + i * 4 + c]; keep[i * 4 + c] = rank ? acc[40 + i * 4 + c] : acc[i * 4 + c]; }
            asm volatile("st.shared::cluster.v4.f32 [%0], {%1,%2,%3,%4};" :: "r"(remote + i * 4096), "f"(v[0]), "f"(v[1]), "f"(v[2]), "f"(v[3]) : "memory");
        }
        asm volatile("barrier.cluster.arrive.release.aligned;" ::: "memory");
        mbar_wait(sRes, 0);
        asm volatile("barrier.cluster.wait.acquire.aligned;" ::: "memory");
        #pragma unroll
        for (int i = 0; i < 10; i++) {
            const uint4 v = lds128(sX + tid * 16 + i * 4096);
            keep[i * 4] += __uint_as_float(v.x); keep[i * 4 + 1] += __uint_as_float(v.y); keep[i * 4 + 2] += __uint_as_float(v.z); keep[i * 4 + 3] += __uint_as_float(v.w);
        }
        resid_add_store(keep, sR + wg * 10240, warp, lane);
        proxy_fence();
        bar_sync(1 + wg, 128);
        if ((tid & 127) == 0) {
            tma_store(&tmOut, sR + wg * 10240, cg * 128 + wg * 64, tb * 160 + rank * 80);
            tma_store_commit_wait();
        }
    }
}

typedef CUresult (*EncodeFn)(CUtensorMap*, CUtensorMapDataType, cuuint32_t, void*, const cuuint64_t*, const cuuint64_t*, const cuuint32_t*,
                             const cuuint32_t*, CUtensorMapInterleave, CUtensorMapSwizzle, CUtensorMapL2promotion, CUtensorMapFloatOOBfill);

CUtensorMap make_map(EncodeFn enc, const void* p, int cols, int rows, int bc, int br) {
    CUtensorMap tm;
    cuuint64_t gd[2] = {(cuuint64_t)cols, (cuuint64_t)rows};
    cuuint64_t gs[1] = {(cuuint64_t)cols * 2};
    cuuint32_t box[2] = {(cuuint32_t)bc, (cuuint32_t)br}, es[2] = {1, 1};
    enc(&tm, CU_TENSOR_MAP_DATA_TYPE_BFLOAT16, 2, const_cast<void*>(p), gd, gs, box, es, CU_TENSOR_MAP_INTERLEAVE_NONE,
        bc == 64 ? CU_TENSOR_MAP_SWIZZLE_128B : CU_TENSOR_MAP_SWIZZLE_64B, CU_TENSOR_MAP_L2_PROMOTION_L2_128B, CU_TENSOR_MAP_FLOAT_OOB_FILL_NONE);
    return tm;
}

template<typename... KArgs, typename... Args>
void launch(void (*kern)(KArgs...), int grid, int block, int smem, bool pdl, Args... args) {
    cudaLaunchConfig_t cfg = {};
    cfg.gridDim = dim3(grid); cfg.blockDim = dim3(block); cfg.dynamicSmemBytes = smem; cfg.stream = cudaStreamPerThread;
    cudaLaunchAttribute at[1];
    at[0].id = cudaLaunchAttributeProgrammaticStreamSerialization;
    at[0].val.programmaticStreamSerializationAllowed = 1;
    cfg.attrs = at; cfg.numAttrs = pdl ? 1 : 0;
    cudaLaunchKernelEx(&cfg, kern, args...);
}

}

extern "C" void kernel_launch(void* const* d_in, const int* in_sizes, int n_in, void* d_out, int out_size) {
    (void)in_sizes; (void)n_in; (void)out_size;
    const __nv_bfloat16* x = (const __nv_bfloat16*)d_in[0];
    const __nv_bfloat16* wqkv = (const __nv_bfloat16*)d_in[1];
    const __nv_bfloat16* wo = (const __nv_bfloat16*)d_in[2];
    const __nv_bfloat16* wg = (const __nv_bfloat16*)d_in[4];
    const __nv_bfloat16* wu = (const __nv_bfloat16*)d_in[5];
    const __nv_bfloat16* wd = (const __nv_bfloat16*)d_in[6];
    static EncodeFn enc = nullptr;
    if (!enc) {
        void* fn = nullptr;
        cudaDriverEntryPointQueryResult qr;
        cudaGetDriverEntryPoint("cuTensorMapEncodeTiled", &fn, cudaEnableDefault, &qr);
        enc = (EncodeFn)fn;
        cudaFuncSetAttribute(k1_qkv, cudaFuncAttributeMaxDynamicSharedMemorySize, K1_SMEM);
        cudaFuncSetAttribute(k2_attn, cudaFuncAttributeMaxDynamicSharedMemorySize, K2_SMEM);
        cudaFuncSetAttribute(k3_wo, cudaFuncAttributeMaxDynamicSharedMemorySize, K3_SMEM);
        cudaFuncSetAttribute(k4_glu, cudaFuncAttributeMaxDynamicSharedMemorySize, K4_SMEM);
        cudaFuncSetAttribute(k5_down, cudaFuncAttributeMaxDynamicSharedMemorySize, K5_SMEM);
    }
    void *po, *ph, *phh;
    cudaGetSymbolAddress(&po, g_o); cudaGetSymbolAddress(&ph, g_h); cudaGetSymbolAddress(&phh, g_hh);
    const CUtensorMap tmX = make_map(enc, x, DM, SEQ, 64, 128), tmW = make_map(enc, wqkv, NQKV, DM, 64, 64);
    const CUtensorMap tmWo = make_map(enc, wo, DM, DM, 64, 64), tmO = make_map(enc, po, DM, SEQ, 64, 80);
    const CUtensorMap tmXr = make_map(enc, x, DM, SEQ, 64, 80), tmH80 = make_map(enc, ph, DM, SEQ, 64, 80);
    const CUtensorMap tmH = make_map(enc, ph, DM, SEQ, 64, 128);
    const CUtensorMap tmG64 = make_map(enc, wg, FF, DM, 64, 64), tmU64 = make_map(enc, wu, FF, DM, 64, 64);
    const CUtensorMap tmG32 = make_map(enc, wg, FF, DM, 32, 64), tmU32 = make_map(enc, wu, FF, DM, 32, 64);
    const CUtensorMap tmWd = make_map(enc, wd, DM, FF, 64, 64), tmHH = make_map(enc, phh, FF, SEQ, 64, 160);
    const CUtensorMap tmOut = make_map(enc, d_out, DM, SEQ, 64, 80);

    launch(k0_prep, 128, 256, 0, false, x, wqkv);
    launch(k1_qkv, 128, 256, K1_SMEM, true, tmX, tmW);
    launch(k2_attn, 132, 384, K2_SMEM, true, wo, wg, wu, wd);
    launch(k3_wo, 130, 288, K3_SMEM, true, tmWo, tmO, tmXr, tmH80);
    launch(k4_glu, 128, 384, K4_SMEM, true, tmH, tmG64, tmU64, tmG32, tmU32);
    launch(k5_down, 130, 288, K5_SMEM, true, tmWd, tmHH, tmH80, tmOut);
}
```

```cpp
#include <cuda_runtime.h>
#include <cuda_bf16.h>
#include <cuda.h>
#include <stdint.h>

namespace {

constexpr int SEQ = 2048, DM = 640, NH = 32, HD = 20, FF = 1728, NQKV = 1920;
constexpr int Q_HEAD = 16 * 6144, KV_HEAD = 16 * 12288;
constexpr float LN_EPS = 1e-5f;
constexpr float QSCALE = 0.22360679774997896f * 1.4426950408889634f;
#define MUFU_MASK 0x03

__device__ __align__(1024) uint8_t g_q[NH * Q_HEAD];
__device__ __align__(1024) uint8_t g_kv[NH * KV_HEAD];
__device__ __align__(1024) __nv_bfloat16 g_o[SEQ * DM];
__device__ __align__(1024) __nv_bfloat16 g_h[SEQ * DM];
__device__ __align__(128) float2 g_st2[10 * 2080];
__device__ __align__(128) float g_rs2[2080];
__device__ __align__(16) float g_cs2[2 * FF];
__device__ __align__(1024) __nv_bfloat16 g_hh[SEQ * FF];
__device__ uint32_t g_zero[2] = {0u, 0u};

__device__ __forceinline__ uint32_t smem_u32(const void* p) { return (uint32_t)__cvta_generic_to_shared(p); }
__device__ __forceinline__ uint32_t opaque(uint32_t x) { uint32_t r; asm volatile("mov.u32 %0, %1;" : "=r"(r) : "r"(x)); return r; }
__device__ __forceinline__ void mbar_init(uint32_t bar, uint32_t cnt) { asm volatile("mbarrier.init.shared::cta.b64 [%0], %1;" :: "r"(bar), "r"(cnt) : "memory"); }
template<int N> __device__ __forceinline__ void mbar_init_n(uint32_t bar, uint32_t cnt) {
    #pragma unroll
    for (int i = 0; i < N; i++) mbar_init(bar + i * 8, cnt);
    asm volatile("fence.mbarrier_init.release.cluster;" ::: "memory");
}
__device__ __forceinline__ void mbar_expect(uint32_t bar, uint32_t bytes) { asm volatile("mbarrier.arrive.expect_tx.shared::cta.b64 _, [%0], %1;" :: "r"(bar), "r"(bytes) : "memory"); }
__device__ __forceinline__ void mbar_arrive(uint32_t bar) { asm volatile("mbarrier.arrive.shared::cta.b64 _, [%0];" :: "r"(bar) : "memory"); }
__device__ __forceinline__ bool mbar_try(uint32_t bar, uint32_t parity) {
    uint32_t done;
    asm volatile("{\n.reg .pred p;\nmbarrier.try_wait.parity.shared::cta.b64 p, [%1], %2;\nselp.u32 %0, 1, 0, p;\n}\n" : "=r"(done) : "r"(bar), "r"(parity) : "memory");
    return done;
}
__device__ __forceinline__ void mbar_wait(uint32_t bar, uint32_t parity) {
    if (mbar_try(bar, parity)) return;
    uint32_t n = 0;
    while (!mbar_try(bar, parity)) { if (++n > (1u << 22)) __trap(); }
}
__device__ __forceinline__ bool elect_one() { uint32_t p; asm volatile("{\n.reg .pred P;\nelect.sync _|P, 0xffffffff;\nselp.u32 %0, 1, 0, P;\n}\n" : "=r"(p)); return p; }
__device__ __forceinline__ void bulk_g2s(uint32_t dst, const void* src, uint32_t bytes, uint32_t bar) {
    asm volatile("cp.async.bulk.shared::cluster.global.mbarrier::complete_tx::bytes [%0], [%1], %2, [%3];" :: "r"(dst), "l"(src), "r"(bytes), "r"(bar) : "memory");
}
__device__ __forceinline__ void tma_load(uint32_t dst, const CUtensorMap* tm, uint32_t bar, int c0, int c1) {
    asm volatile("cp.async.bulk.tensor.2d.shared::cluster.global.mbarrier::complete_tx::bytes [%0], [%1, {%3, %4}], [%2];"
        :: "r"(dst), "l"(tm), "r"(bar), "r"(c0), "r"(c1) : "memory");
}
__device__ __forceinline__ void tma_load5(uint32_t dst, const CUtensorMap* tm, uint32_t bar, int c0, int c4) {
    asm volatile("cp.async.bulk.tensor.5d.shared::cluster.global.mbarrier::complete_tx::bytes [%0], [%1, {%3, %5, %5, %5, %4}], [%2];"
        :: "r"(dst), "l"(tm), "r"(bar), "r"(c0), "r"(c4), "r"(0) : "memory");
}
__device__ __forceinline__ void tma_store(const CUtensorMap* tm, uint32_t src, int c0, int c1) {
    asm volatile("cp.async.bulk.tensor.2d.global.shared::cta.bulk_group [%0, {%2, %3}], [%1];" :: "l"(tm), "r"(src), "r"(c0), "r"(c1) : "memory");
}
__device__ __forceinline__ void tma_store_commit_wait() {
    asm volatile("cp.async.bulk.commit_group;" ::: "memory");
    asm volatile("cp.async.bulk.wait_group.read 0;" ::: "memory");
}
__device__ __forceinline__ void bulk_s2g(void* dst, uint32_t src, uint32_t bytes) {
    asm volatile("cp.async.bulk.global.shared::cta.bulk_group [%0], [%1], %2;" :: "l"(dst), "r"(src), "r"(bytes) : "memory");
}
__device__ __forceinline__ void tmap_prefetch(const CUtensorMap* tm) { asm volatile("prefetch.tensormap [%0];" :: "l"(tm) : "memory"); }
__device__ __forceinline__ void pdl_launch() { asm volatile("griddepcontrol.launch_dependents;" ::: "memory"); }
__device__ __forceinline__ void pdl_wait() { asm volatile("griddepcontrol.wait;" ::: "memory"); }
__device__ __forceinline__ void proxy_fence() { asm volatile("fence.proxy.async.shared::cta;" ::: "memory"); }
__device__ __forceinline__ void bar_sync(int id, int n) { asm volatile("bar.sync %0, %1;" :: "r"(id), "r"(n) : "memory"); }
__device__ __forceinline__ void bar_arrive(int id, int n) { asm volatile("bar.arrive %0, %1;" :: "r"(id), "r"(n) : "memory"); }
__device__ __forceinline__ void wg_fence() { asm volatile("wgmma.fence.sync.aligned;" ::: "memory"); }
__device__ __forceinline__ void wg_commit() { asm volatile("wgmma.commit_group.sync.aligned;" ::: "memory"); }
template<int N> __device__ __forceinline__ void wg_wait() { asm volatile("wgmma.wait_group.sync.aligned %0;" :: "n"(N) : "memory"); }
template<int N> __device__ __forceinline__ void pin(float (&d)[N]) {
    #pragma unroll
    for (int i = 0; i < N; i++) asm volatile("" : "+f"(d[i]) :: "memory");
}
template<int N> __device__ __forceinline__ void pin(uint32_t (&d)[N]) {
    #pragma unroll
    for (int i = 0; i < N; i++) asm volatile("" : "+r"(d[i]) :: "memory");
}
__device__ __forceinline__ uint64_t mkdesc(uint32_t addr, uint32_t lbo, uint32_t sbo, uint32_t swz) {
    return (uint64_t)((addr & 0x3FFFF) >> 4) | ((uint64_t)(lbo >> 4) << 16) | ((uint64_t)(sbo >> 4) << 32) | ((uint64_t)swz << 62);
}
__device__ __forceinline__ uint32_t pack_bf16(float lo, float hi) { uint32_t r; asm("cvt.rn.bf16x2.f32 %0, %1, %2;" : "=r"(r) : "f"(hi), "f"(lo)); return r; }
__device__ __forceinline__ float ex2(float x) { float r; asm("ex2.approx.ftz.f32 %0, %1;" : "=f"(r) : "f"(x)); return r; }
__device__ __forceinline__ float bf_lo(uint32_t v) { return __uint_as_float(v << 16); }
__device__ __forceinline__ float bf_hi(uint32_t v) { return __uint_as_float(v & 0xFFFF0000u); }
__device__ __forceinline__ float round_bf16(float x) { return bf_lo(pack_bf16(x, 0.f)); }
__device__ __forceinline__ uint4 lds128(uint32_t a) { uint4 v; asm volatile("ld.shared.v4.u32 {%0,%1,%2,%3}, [%4];" : "=r"(v.x), "=r"(v.y), "=r"(v.z), "=r"(v.w) : "r"(a) : "memory"); return v; }
__device__ __forceinline__ void ldsm_x4_t(uint32_t a, uint32_t& r0, uint32_t& r1, uint32_t& r2, uint32_t& r3) {
    asm volatile("ldmatrix.sync.aligned.m8n8.x4.trans.shared.b16 {%0,%1,%2,%3}, [%4];" : "=r"(r0), "=r"(r1), "=r"(r2), "=r"(r3) : "r"(a) : "memory");
}
__device__ __forceinline__ void stsm_x4_t(uint32_t a, uint32_t r0, uint32_t r1, uint32_t r2, uint32_t r3) {
    asm volatile("stmatrix.sync.aligned.m8n8.x4.trans.shared.b16 [%0], {%1,%2,%3,%4};" :: "r"(a), "r"(r0), "r"(r1), "r"(r2), "r"(r3) : "memory");
}

__device__ __forceinline__ void wg_SS128_01(float (&d)[64], uint64_t da, uint64_t db, int sd) {
  asm volatile("{\n.reg .pred p;\nsetp.ne.b32 p, %66, 0;\n"
    "wgmma.mma_async.sync.aligned.m64n128k16.f32.bf16.bf16 {%0,%1,%2,%3,%4,%5,%6,%7,%8,%9,%10,%11,%12,%13,%14,%15,%16,%17,%18,%19,%20,%21,%22,%23,%24,%25,%26,%27,%28,%29,%30,%31,%32,%33,%34,%35,%36,%37,%38,%39,%40,%41,%42,%43,%44,%45,%46,%47,%48,%49,%50,%51,%52,%53,%54,%55,%56,%57,%58,%59,%60,%61,%62,%63}, %64, %65, p, 1, 1, 0, 1;\n}\n"
    : "+f"(d[0]),"+f"(d[1]),"+f"(d[2]),"+f"(d[3]),"+f"(d[4]),"+f"(d[5]),"+f"(d[6]),"+f"(d[7]),"+f"(d[8]),"+f"(d[9]),"+f"(d[10]),"+f"(d[11]),"+f"(d[12]),"+f"(d[13]),"+f"(d[14]),"+f"(d[15]),"+f"(d[16]),"+f"(d[17]),"+f"(d[18]),"+f"(d[19]),"+f"(d[20]),"+f"(d[21]),"+f"(d[22]),"+f"(d[23]),"+f"(d[24]),"+f"(d[25]),"+f"(d[26]),"+f"(d[27]),"+f"(d[28]),"+f"(d[29]),"+f"(d[30]),"+f"(d[31]),"+f"(d[32]),"+f"(d[33]),"+f"(d[34]),"+f"(d[35]),"+f"(d[36]),"+f"(d[37]),"+f"(d[38]),"+f"(d[39]),"+f"(d[40]),"+f"(d[41]),"+f"(d[42]),"+f"(d[43]),"+f"(d[44]),"+f"(d[45]),"+f"(d[46]),"+f"(d[47]),"+f"(d[48]),"+f"(d[49]),"+f"(d[50]),"+f"(d[51]),"+f"(d[52]),"+f"(d[53]),"+f"(d[54]),"+f"(d[55]),"+f"(d[56]),"+f"(d[57]),"+f"(d[58]),"+f"(d[59]),"+f"(d[60]),"+f"(d[61]),"+f"(d[62]),"+f"(d[63])
    : "l"(da), "l"(db), "r"(sd));
}
__device__ __forceinline__ void wg_SS128_00(float (&d)[64], uint64_t da, uint64_t db, int sd) {
  asm volatile("{\n.reg .pred p;\nsetp.ne.b32 p, %66, 0;\n"
    "wgmma.mma_async.sync.aligned.m64n128k16.f32.bf16.bf16 {%0,%1,%2,%3,%4,%5,%6,%7,%8,%9,%10,%11,%12,%13,%14,%15,%16,%17,%18,%19,%20,%21,%22,%23,%24,%25,%26,%27,%28,%29,%30,%31,%32,%33,%34,%35,%36,%37,%38,%39,%40,%41,%42,%43,%44,%45,%46,%47,%48,%49,%50,%51,%52,%53,%54,%55,%56,%57,%58,%59,%60,%61,%62,%63}, %64, %65, p, 1, 1, 0, 0;\n}\n"
    : "+f"(d[0]),"+f"(d[1]),"+f"(d[2]),"+f"(d[3]),"+f"(d[4]),"+f"(d[5]),"+f"(d[6]),"+f"(d[7]),"+f"(d[8]),"+f"(d[9]),"+f"(d[10]),"+f"(d[11]),"+f"(d[12]),"+f"(d[13]),"+f"(d[14]),"+f"(d[15]),"+f"(d[16]),"+f"(d[17]),"+f"(d[18]),"+f"(d[19]),"+f"(d[20]),"+f"(d[21]),"+f"(d[22]),"+f"(d[23]),"+f"(d[24]),"+f"(d[25]),"+f"(d[26]),"+f"(d[27]),"+f"(d[28]),"+f"(d[29]),"+f"(d[30]),"+f"(d[31]),"+f"(d[32]),"+f"(d[33]),"+f"(d[34]),"+f"(d[35]),"+f"(d[36]),"+f"(d[37]),"+f"(d[38]),"+f"(d[39]),"+f"(d[40]),"+f"(d[41]),"+f"(d[42]),"+f"(d[43]),"+f"(d[44]),"+f"(d[45]),"+f"(d[46]),"+f"(d[47]),"+f"(d[48]),"+f"(d[49]),"+f"(d[50]),"+f"(d[51]),"+f"(d[52]),"+f"(d[53]),"+f"(d[54]),"+f"(d[55]),"+f"(d[56]),"+f"(d[57]),"+f"(d[58]),"+f"(d[59]),"+f"(d[60]),"+f"(d[61]),"+f"(d[62]),"+f"(d[63])
    : "l"(da), "l"(db), "r"(sd));
}
__device__ __forceinline__ void wg_SS64_01(float (&d)[32], uint64_t da, uint64_t db, int sd) {
  asm volatile("{\n.reg .pred p;\nsetp.ne.b32 p, %34, 0;\n"
    "wgmma.mma_async.sync.aligned.m64n64k16.f32.bf16.bf16 {%0,%1,%2,%3,%4,%5,%6,%7,%8,%9,%10,%11,%12,%13,%14,%15,%16,%17,%18,%19,%20,%21,%22,%23,%24,%25,%26,%27,%28,%29,%30,%31}, %32, %33, p, 1, 1, 0, 1;\n}\n"
    : "+f"(d[0]),"+f"(d[1]),"+f"(d[2]),"+f"(d[3]),"+f"(d[4]),"+f"(d[5]),"+f"(d[6]),"+f"(d[7]),"+f"(d[8]),"+f"(d[9]),"+f"(d[10]),"+f"(d[11]),"+f"(d[12]),"+f"(d[13]),"+f"(d[14]),"+f"(d[15]),"+f"(d[16]),"+f"(d[17]),"+f"(d[18]),"+f"(d[19]),"+f"(d[20]),"+f"(d[21]),"+f"(d[22]),"+f"(d[23]),"+f"(d[24]),"+f"(d[25]),"+f"(d[26]),"+f"(d[27]),"+f"(d[28]),"+f"(d[29]),"+f"(d[30]),"+f"(d[31])
    : "l"(da), "l"(db), "r"(sd));
}
__device__ __forceinline__ void wg_SS64_00(float (&d)[32], uint64_t da, uint64_t db, int sd) {
  asm volatile("{\n.reg .pred p;\nsetp.ne.b32 p, %34, 0;\n"
    "wgmma.mma_async.sync.aligned.m64n64k16.f32.bf16.bf16 {%0,%1,%2,%3,%4,%5,%6,%7,%8,%9,%10,%11,%12,%13,%14,%15,%16,%17,%18,%19,%20,%21,%22,%23,%24,%25,%26,%27,%28,%29,%30,%31}, %32, %33, p, 1, 1, 0, 0;\n}\n"
    : "+f"(d[0]),"+f"(d[1]),"+f"(d[2]),"+f"(d[3]),"+f"(d[4]),"+f"(d[5]),"+f"(d[6]),"+f"(d[7]),"+f"(d[8]),"+f"(d[9]),"+f"(d[10]),"+f"(d[11]),"+f"(d[12]),"+f"(d[13]),"+f"(d[14]),"+f"(d[15]),"+f"(d[16]),"+f"(d[17]),"+f"(d[18]),"+f"(d[19]),"+f"(d[20]),"+f"(d[21]),"+f"(d[22]),"+f"(d[23]),"+f"(d[24]),"+f"(d[25]),"+f"(d[26]),"+f"(d[27]),"+f"(d[28]),"+f"(d[29]),"+f"(d[30]),"+f"(d[31])
    : "l"(da), "l"(db), "r"(sd));
}
__device__ __forceinline__ void wg_SS80_10(float (&d)[40], uint64_t da, uint64_t db, int sd) {
  asm volatile("{\n.reg .pred p;\nsetp.ne.b32 p, %42, 0;\n"
    "wgmma.mma_async.sync.aligned.m64n80k16.f32.bf16.bf16 {%0,%1,%2,%3,%4,%5,%6,%7,%8,%9,%10,%11,%12,%13,%14,%15,%16,%17,%18,%19,%20,%21,%22,%23,%24,%25,%26,%27,%28,%29,%30,%31,%32,%33,%34,%35,%36,%37,%38,%39}, %40, %41, p, 1, 1, 1, 0;\n}\n"
    : "+f"(d[0]),"+f"(d[1]),"+f"(d[2]),"+f"(d[3]),"+f"(d[4]),"+f"(d[5]),"+f"(d[6]),"+f"(d[7]),"+f"(d[8]),"+f"(d[9]),"+f"(d[10]),"+f"(d[11]),"+f"(d[12]),"+f"(d[13]),"+f"(d[14]),"+f"(d[15]),"+f"(d[16]),"+f"(d[17]),"+f"(d[18]),"+f"(d[19]),"+f"(d[20]),"+f"(d[21]),"+f"(d[22]),"+f"(d[23]),"+f"(d[24]),"+f"(d[25]),"+f"(d[26]),"+f"(d[27]),"+f"(d[28]),"+f"(d[29]),"+f"(d[30]),"+f"(d[31]),"+f"(d[32]),"+f"(d[33]),"+f"(d[34]),"+f"(d[35]),"+f"(d[36]),"+f"(d[37]),"+f"(d[38]),"+f"(d[39])
    : "l"(da), "l"(db), "r"(sd));
}
__device__ __forceinline__ void wg_RS64_00(float (&d)[32], uint32_t a0, uint32_t a1, uint32_t a2, uint32_t a3, uint64_t db, int sd) {
  asm volatile("{\n.reg .pred p;\nsetp.ne.b32 p, %37, 0;\n"
    "wgmma.mma_async.sync.aligned.m64n64k16.f32.bf16.bf16 {%0,%1,%2,%3,%4,%5,%6,%7,%8,%9,%10,%11,%12,%13,%14,%15,%16,%17,%18,%19,%20,%21,%22,%23,%24,%25,%26,%27,%28,%29,%30,%31}, {%32,%33,%34,%35}, %36, p, 1, 1, 0;\n}\n"
    : "+f"(d[0]),"+f"(d[1]),"+f"(d[2]),"+f"(d[3]),"+f"(d[4]),"+f"(d[5]),"+f"(d[6]),"+f"(d[7]),"+f"(d[8]),"+f"(d[9]),"+f"(d[10]),"+f"(d[11]),"+f"(d[12]),"+f"(d[13]),"+f"(d[14]),"+f"(d[15]),"+f"(d[16]),"+f"(d[17]),"+f"(d[18]),"+f"(d[19]),"+f"(d[20]),"+f"(d[21]),"+f"(d[22]),"+f"(d[23]),"+f"(d[24]),"+f"(d[25]),"+f"(d[26]),"+f"(d[27]),"+f"(d[28]),"+f"(d[29]),"+f"(d[30]),"+f"(d[31])
    : "r"(a0), "r"(a1), "r"(a2), "r"(a3), "l"(db), "r"(sd));
}
__device__ __forceinline__ void wg_RS24_01(float (&d)[12], uint32_t a0, uint32_t a1, uint32_t a2, uint32_t a3, uint64_t db, int sd) {
  asm volatile("{\n.reg .pred p;\nsetp.ne.b32 p, %17, 0;\n"
    "wgmma.mma_async.sync.aligned.m64n24k16.f32.bf16.bf16 {%0,%1,%2,%3,%4,%5,%6,%7,%8,%9,%10,%11}, {%12,%13,%14,%15}, %16, p, 1, 1, 1;\n}\n"
    : "+f"(d[0]),"+f"(d[1]),"+f"(d[2]),"+f"(d[3]),"+f"(d[4]),"+f"(d[5]),"+f"(d[6]),"+f"(d[7]),"+f"(d[8]),"+f"(d[9]),"+f"(d[10]),"+f"(d[11])
    : "r"(a0), "r"(a1), "r"(a2), "r"(a3), "l"(db), "r"(sd));
}

constexpr int NSM = 132;
__device__ unsigned int g_epoch;
__device__ uint32_t g_rank[256];
__device__ uint32_t g_place[256];
__device__ unsigned int g_started[2];

__device__ __forceinline__ uint32_t sm_id() { uint32_t s; asm volatile("mov.u32 %0, %smid;" : "=r"(s)); return s; }
__device__ __forceinline__ uint32_t place_entry(bool placed) {
    uint32_t v = blockIdx.x;
    if (placed) asm volatile("ld.relaxed.gpu.global.u32 %0, [%1];" : "=r"(v) : "l"(g_place + sm_id()) : "memory");
    return v;
}
__device__ __forceinline__ void place_guard(unsigned int* cnt, uint32_t entry) {
    const unsigned int n = atomicAdd(cnt, 1u) / NSM + 1;
    if ((entry >> 8) != (n & 0xFFFFFFu)) __trap();
    unsigned int c, i = 0;
    do {
        asm volatile("ld.relaxed.gpu.global.u32 %0, [%1];" : "=r"(c) : "l"(cnt) : "memory");
        if (++i > (1u << 22)) __trap();
        __nanosleep(200);
    } while ((int)(c - n * NSM) < 0);
}

__device__ unsigned long long g_xst[SEQ * 2];
__device__ unsigned long long g_xcs[4 * NQKV];

__device__ __forceinline__ void st_tag(unsigned long long* p, float v, uint32_t tag) {
    asm volatile("st.relaxed.gpu.global.b64 [%0], %1;" :: "l"(p), "l"(((unsigned long long)tag << 32) | __float_as_uint(v)) : "memory");
}
__device__ __forceinline__ unsigned long long ld_tag(const unsigned long long* p) {
    unsigned long long v;
    asm volatile("ld.relaxed.gpu.global.b64 %0, [%1];" : "=l"(v) : "l"(p) : "memory");
    return v;
}

constexpr int K1_NST = 5, K1_RING = K1_NST * 32768, K1_IMG = K1_RING, K1_MISC = K1_IMG + 8 * 6144;
constexpr int K1_FIX = K1_MISC + 4096;
constexpr int K1_SMEM = K1_FIX + 4096 + 8192;

template<int V>
__device__ __forceinline__ void k1_epilogue(const float (&a0)[64], const float (&a1)[64], const float* st, float sc, int part,
                                            uint32_t img, uint32_t img6, int warp, int lane) {
    const int c4 = (lane & 3) * 4;
    const bool lo = (lane & 2) == 0;
    #pragma unroll
    for (int mt = 0; mt < 2; mt++) {
        const float (&acc)[64] = mt ? a1 : a0;
        const int r0 = mt * 64 + warp * 16 + (lane >> 2);
        const float a = st[r0] * sc, b = st[r0 + 8] * sc;
        uint32_t pb[2][5];
        #pragma unroll
        for (int hf = 0; hf < 2; hf++) {
            const int g = mt * 8 + warp * 2 + hf, rr = (lane >> 2) * 16;
            const uint32_t b0 = rr + (part == 0 ? g * 128 : part == 1 ? g * 256 : (g >> 1) * 768 + hf * 128);
            const uint32_t b1 = b0 + (part == 0 ? 2048 : part == 1 ? 128 : 256);
            const uint32_t b2 = part == 0 ? b0 + 4096 : part == 1 ? rr + 4096 + (g & 7) * 256 + mt * 128 : b0 + 512;
            pb[hf][0] = b0 + c4; pb[hf][1] = b1 + c4;
            pb[hf][2] = lo ? b2 + c4 : b0 + 6144 + c4 - 8;
            pb[hf][3] = lo ? b0 + 8 + c4 : b1 + c4 - 8;
            pb[hf][4] = lo ? b1 + 8 + c4 : b2 + c4 - 8;
        }
        #pragma unroll
        for (int j = 0; j < 16; j++) {
            const int col = V == 0 ? j * 8 : V == 1 ? 128 + j * 8 : (j >> 3) * 80 + 16 + (j & 7) * 8;
            const int slot = col / 20, d0 = col % 20, pat = d0 == 0 ? 0 : d0 == 8 ? 1 : d0 == 16 ? 2 : d0 == 4 ? 3 : 4;
            const uint32_t p0 = pack_bf16(acc[j * 4] * a, acc[j * 4 + 1] * a), p1 = pack_bf16(acc[j * 4 + 2] * b, acc[j * 4 + 3] * b);
            uint32_t base = img;
            if (V == 1 && slot == 6) base = (pat == 2 && !lo) ? img : img6;
            asm volatile("st.shared.u32 [%0], %1;" :: "r"(base + pb[0][pat] + slot * 6144), "r"(p0));
            asm volatile("st.shared.u32 [%0], %1;" :: "r"(base + pb[1][pat] + slot * 6144), "r"(p1));
        }
        const int g = mt * 8 + warp * 2 + ((lane >> 3) & 1);
        const bool emu = !((MUFU_MASK >> (g & 7)) & 1);
        const uint32_t e0 = part == 0 ? 0x3F803F80u : part == 2 ? 0x00003F80u : emu ? ((lane & 1) ? 0x43E04780u : 0x429E4780u) : 0xC23A0000u;
        const uint32_t e1 = part == 0 ? 0x00003F80u : part == 2 ? 0u : emu ? 0x00003B80u : 0x00003DAEu;
        const uint32_t ea = (lane & 7) * 16 + 8 + (part == 0 ? 4096 + g * 128 : part == 1 ? 4096 + (g & 7) * 256 + mt * 128 : (g >> 1) * 768 + (g & 1) * 128 + 512);
        #pragma unroll
        for (int i = 0; i < (V == 2 ? 4 : 3); i++) {
            const int slot = (V == 1 ? 6 : 0) + i * 2 + (lane >> 4);
            asm volatile("st.shared.v2.u32 [%0], {%1,%2};" :: "r"((V == 1 && slot == 6 ? img6 : img) + ea + slot * 6144), "r"(e0), "r"(e1));
        }
    }
}

__global__ void __launch_bounds__(288, 1)
k1_qkv(const __grid_constant__ CUtensorMap tmX, const __grid_constant__ CUtensorMap tmW, const __nv_bfloat16* __restrict__ x, const __nv_bfloat16* __restrict__ wqkv) {
    extern __shared__ __align__(1024) uint8_t smem[];
    const uint32_t sb = opaque(smem_u32(smem));
    const uint32_t sFull = sb + K1_MISC + 3584, sEmpty = sFull + 64;
    float* const sSt = (float*)(smem + K1_MISC);
    const int tid = threadIdx.x, lane = tid & 31;
    const int warp = __shfl_sync(0xffffffff, tid >> 5, 0);
    const int mb = blockIdx.x >> 3, nt = blockIdx.x & 7;
    const int atom0 = nt < 6 ? nt * 5 : nt * 20 - 116, astep = nt < 6 ? 1 : 5;
    const int npass = nt == 7 ? 1 : 2;
    auto load_stage = [&](int s, int st) {
        const bool keep = s >= 10 && s < 10 + K1_NST;
        const int kb = s < 10 ? s : keep ? s - K1_NST : s - 10 - K1_NST, at = atom0 + (s < 10 ? 0 : 2 * astep);
        const uint32_t base = sb + st * 32768, bar = sFull + st * 8;
        mbar_expect(bar, keep ? 16384 : 32768);
        if (!keep) tma_load(base, &tmX, bar, kb * 64, mb * 128);
        tma_load(base + 16384, &tmW, bar, at * 64, kb * 64);
        tma_load(base + 24576, &tmW, bar, (at + astep) * 64, kb * 64);
    };
    if (warp == 8 && elect_one()) { mbar_init_n<K1_NST>(sFull, 1); load_stage(0, 0); }
    if (warp == 0 && elect_one()) mbar_init_n<K1_NST>(sEmpty, 1);
    __syncthreads();
    pdl_launch();
    if (warp == 8) {
        #pragma unroll 1
        for (int s = 1, st = 1, ph = 1; s < npass * 10; s++) {
            if (s >= K1_NST) mbar_wait(sEmpty + st * 8, ph);
            if (elect_one()) load_stage(s, st);
            __syncwarp();
            if (++st == K1_NST) { st = 0; ph ^= 1; }
        }
        return;
    }
    const int wg = warp >> 2;
    uint32_t tag;
    asm volatile("ld.relaxed.gpu.global.u32 %0, [%1];" : "=r"(tag) : "l"(&g_epoch) : "memory");
    tag += 1;
    if (tid == 0) g_rank[sm_id() & 255] = (tag << 8) | blockIdx.x;
    if (wg == 1) {
        const int t = tid - 128;
        float (*red)[64] = (float (*)[64])(smem + K1_MISC + 2560);
        __nanosleep(250);
        uint2 xr[4][5];
        uint4 wr[10];
        const bool docs = blockIdx.x < 120;
        const int catom = blockIdx.x % 30, kq = blockIdx.x / 30;
        #pragma unroll
        for (int r = 0; r < 4; r++) {
            const uint2* p = (const uint2*)(x + (size_t)(blockIdx.x * 16 + (warp - 4) * 4 + r) * DM) + lane;
            #pragma unroll
            for (int i = 0; i < 5; i++) xr[r][i] = __ldg(p + i * 32);
        }
        if (docs) {
            const uint4* p = (const uint4*)(wqkv + (size_t)(kq * 160 + (t >> 3)) * NQKV + catom * 64 + (t & 7) * 8);
            #pragma unroll
            for (int i = 0; i < 10; i++) wr[i] = __ldg(p + (size_t)i * 16 * (NQKV / 8));
        }
        float s[4], q[4];
        #pragma unroll
        for (int r = 0; r < 4; r++) {
            s[r] = 0.f;
            #pragma unroll
            for (int i = 0; i < 5; i++) s[r] += (bf_lo(xr[r][i].x) + bf_hi(xr[r][i].x)) + (bf_lo(xr[r][i].y) + bf_hi(xr[r][i].y));
        }
        #pragma unroll
        for (int o = 16; o; o >>= 1) {
            #pragma unroll
            for (int r = 0; r < 4; r++) s[r] += __shfl_xor_sync(0xffffffff, s[r], o);
        }
        #pragma unroll
        for (int r = 0; r < 4; r++) {
            s[r] *= (1.f / DM);
            q[r] = 0.f;
            #pragma unroll
            for (int i = 0; i < 5; i++) {
                const float d0 = bf_lo(xr[r][i].x) - s[r], d1 = bf_hi(xr[r][i].x) - s[r], d2 = bf_lo(xr[r][i].y) - s[r], d3 = bf_hi(xr[r][i].y) - s[r];
                q[r] += (d0 * d0 + d1 * d1) + (d2 * d2 + d3 * d3);
            }
        }
        #pragma unroll
        for (int o = 16; o; o >>= 1) {
            #pragma unroll
            for (int r = 0; r < 4; r++) q[r] += __shfl_xor_sync(0xffffffff, q[r], o);
        }
        if (lane < 8) {
            const int r = lane >> 1;
            const float m = r == 0 ? s[0] : r == 1 ? s[1] : r == 2 ? s[2] : s[3], v = r == 0 ? q[0] : r == 1 ? q[1] : r == 2 ? q[2] : q[3];
            const float sd = round_bf16(sqrtf(round_bf16(round_bf16(v * (1.f / DM)) + LN_EPS)));
            st_tag(g_xst + (blockIdx.x * 16 + (warp - 4) * 4) * 2 + lane, (lane & 1) ? 1.f / sd : round_bf16(m), tag);
        }
        if (docs) {
            float c[8];
            #pragma unroll
            for (int j = 0; j < 8; j++) c[j] = 0.f;
            #pragma unroll
            for (int i = 0; i < 10; i++) {
                c[0] += bf_lo(wr[i].x); c[1] += bf_hi(wr[i].x); c[2] += bf_lo(wr[i].y); c[3] += bf_hi(wr[i].y);
                c[4] += bf_lo(wr[i].z); c[5] += bf_hi(wr[i].z); c[6] += bf_lo(wr[i].w); c[7] += bf_hi(wr[i].w);
            }
            #pragma unroll
            for (int o = 8; o < 32; o <<= 1) {
                #pragma unroll
                for (int j = 0; j < 8; j++) c[j] += __shfl_xor_sync(0xffffffff, c[j], o);
            }
            if (lane < 8) {
                #pragma unroll
                for (int j = 0; j < 8; j++) red[warp - 4][lane * 8 + j] = c[j];
            }
            bar_sync(1, 128);
            if (t < 64) st_tag(g_xcs + kq * NQKV + catom * 64 + t, (red[0][t] + red[1][t]) + (red[2][t] + red[3][t]), tag);
        }
        if (npass == 1) return;
        bar_sync(3, 256);
    }
    float a0[64], a1[64];
    {
        const uint64_t dA = mkdesc(sb, 16, 1024, 1), dB = mkdesc(sb + 16384, 8192, 1024, 1);
        #pragma unroll 1
        for (int kb = 0; kb < 10; kb++) {
            const int st = kb < K1_NST ? kb : kb - K1_NST;
            mbar_wait(sFull + st * 8, kb >= K1_NST);
            if (kb == 9 && wg < npass - 1) bar_arrive(3, 256);
            wg_fence();
            const uint64_t so = (uint64_t)(st * 2048);
            #pragma unroll
            for (int k = 0; k < 4; k++) {
                wg_SS128_01(a0, dA + so + k * 2, dB + so + k * 128, k > 0 ? 1 : kb);
                wg_SS128_01(a1, dA + so + 512 + k * 2, dB + so + k * 128, k > 0 ? 1 : kb);
            }
            wg_commit();
            wg_wait<1>();
            if (kb > 0 && (tid & 127) == 0) mbar_arrive(sEmpty + (st ? st - 1 : K1_NST - 1) * 8);
        }
        if (wg == 0) {
            const int t = tid;
            const int at0 = atom0 + (t >> 6) * astep, at1 = at0 + 2 * astep;
            const unsigned long long* p0 = g_xcs + at0 * 64 + (t & 63);
            const unsigned long long* p1 = g_xcs + (at1 < 30 ? at1 : at0) * 64 + (t & 63);
            const unsigned long long* p2 = g_xst + (mb * 128 + t) * 2;
            uint32_t n = 0;
            while (true) {
                unsigned long long v[10];
                #pragma unroll
                for (int i = 0; i < 4; i++) { v[i] = ld_tag(p0 + i * NQKV); v[4 + i] = ld_tag(p1 + i * NQKV); }
                v[8] = ld_tag(p2); v[9] = ld_tag(p2 + 1);
                if (n == 0) {
                    wg_wait<0>();
                    if (tid == 0) mbar_arrive(sEmpty + (K1_NST - 1) * 8);
                }
                bool ok = true;
                #pragma unroll
                for (int i = 0; i < 10; i++) ok = ok && (uint32_t)(v[i] >> 32) == tag;
                if (ok) {
                    const float c0 = (__uint_as_float((uint32_t)v[0]) + __uint_as_float((uint32_t)v[1])) + (__uint_as_float((uint32_t)v[2]) + __uint_as_float((uint32_t)v[3]));
                    const float c1 = (__uint_as_float((uint32_t)v[4]) + __uint_as_float((uint32_t)v[5])) + (__uint_as_float((uint32_t)v[6]) + __uint_as_float((uint32_t)v[7]));
                    const float m = -__uint_as_float((uint32_t)v[8]);
                    const uint32_t mh = pack_bf16(m, m), h0 = pack_bf16(c0, 0.f), h1 = pack_bf16(c1, 0.f);
                    const uint32_t fa = sb + K1_FIX + (t >> 3) * 256 + (t & 7) * 16;
                    asm volatile("st.shared.v4.u32 [%0], {%1,%2,%3,%3};" :: "r"(fa), "r"(mh), "r"(pack_bf16(m - bf_lo(mh), 0.f)), "r"(0u) : "memory");
                    asm volatile("st.shared.v4.u32 [%0], {%1,%2,%3,%3};" :: "r"(fa + 4096), "r"(pack_bf16(c0, c0 - bf_lo(h0))), "r"(h0), "r"(0u) : "memory");
                    asm volatile("st.shared.v4.u32 [%0], {%1,%2,%3,%3};" :: "r"(fa + 8192), "r"(pack_bf16(c1, c1 - bf_lo(h1))), "r"(h1), "r"(0u) : "memory");
                    #pragma unroll
                    for (int i = 0; i < 3; i++) asm volatile("st.shared.v4.u32 [%0], {%1,%1,%1,%1};" :: "r"(fa + i * 4096 + 128), "r"(0u) : "memory");
                    sSt[t] = __uint_as_float((uint32_t)v[9]);
                    proxy_fence();
                    break;
                }
                if (++n > (1u << 20)) __trap();
            }
            __syncwarp();
            bar_sync(5, 128);
            if (npass == 2) bar_arrive(2, 256);
        } else {
            bar_sync(2, 256);
        }
        const uint64_t dF = mkdesc(sb + K1_FIX, 128, 256, 0);
        wg_fence();
        wg_SS128_00(a0, dF, dF + 256 + wg * 256, 1);
        wg_SS128_00(a1, dF + 128, dF + 256 + wg * 256, 1);
        wg_commit();
        wg_wait<0>();
        pin(a0); pin(a1);
    }
    if (wg == 1) bar_sync(1, 128);
    {
        const int part = (atom0 + wg * 2 * astep) / 10;
        const uint32_t img = sb + (wg == 0 ? K1_IMG : nt < 6 ? -7 * 6144 : 0), img6 = sb + K1_IMG;
        const float sc = part == 0 ? QSCALE : 1.f;
        if (nt >= 6) k1_epilogue<2>(a0, a1, sSt, sc, part, img, img6, warp & 3, lane);
        else if (wg == 0) k1_epilogue<0>(a0, a1, sSt, sc, part, img, img6, warp & 3, lane);
        else k1_epilogue<1>(a0, a1, sSt, sc, part, img, img6, warp & 3, lane);
    }
    proxy_fence();
    if (wg == 0) {
        bar_sync(5, 128);
        if (npass == 2) bar_arrive(4, 256);
    } else {
        bar_sync(4, 256);
    }
    if (elect_one()) {
        const int s0 = wg == 0 ? 0 : nt < 6 ? 6 : 8, s1 = nt < 6 ? (wg ? 13 : 6) : s0 + 8, first1 = nt < 6 ? 7 : 8;
        #pragma unroll 1
        for (int slot = s0 + (warp & 3); slot < s1; slot += 4) {
            int part, head, have;
            if (nt < 6) { part = nt >> 1; head = (nt & 1) * 16 + slot; have = slot == 12 ? 3 : 7; }
            else { part = (atom0 + (slot >> 2) * 5) / 10; head = ((slot & 4) ? 28 : 12) + (slot & 3); have = (slot & 3) ? 7 : 4; }
            uint8_t* d = part == 0 ? g_q + head * Q_HEAD + mb * 6144 : g_kv + head * KV_HEAD + mb * 12288 + (part - 1) * 6144;
            const uint32_t a = sb + (slot < first1 ? K1_IMG + slot * 6144 : (slot - first1) * 6144);
            if (have == 7) bulk_s2g(d, a, 6144);
            else if (part < 2) { if (have == 3) bulk_s2g(d, a, 4096); else bulk_s2g(d + 4096, a + 4096, 2048); }
            else {
                const int o = have == 3 ? 0 : 512;
                #pragma unroll 1
                for (int i = 0; i < 8; i++) bulk_s2g(d + i * 768 + o, a + i * 768 + o, have == 3 ? 512 : 256);
            }
        }
        tma_store_commit_wait();
    }
}

__device__ __forceinline__ uint32_t exp2_pair(float t0, float t1, uint32_t sh16) {
    uint32_t y, r;
    asm("mad.lo.u32 %0, %1, %3, %2;" : "=r"(y) : "r"(__float_as_uint(t1)), "r"(__float_as_uint(t0)), "r"(sh16));
    asm("fma.rn.bf16x2 %0, %1, %2, %3;" : "=r"(r) : "r"(y), "r"(y | 0x3F803F80u), "r"(y | 0x007F007Fu));
    return r;
}
constexpr int K2_Q = KV_HEAD, K2_ZERO = K2_Q + 4 * 6144, K2_X = K2_ZERO + 1024, K2_BAR = K2_X + 6144;
constexpr int K2_SMEM = K2_BAR + 128 + 64;
constexpr float SAFE_S = 47.f;
constexpr uint64_t D_TILE = 768, D_KB = 128, D_K2 = 256ull - (8ull << 16), D_K2B = 8, D_V = 384, D_VK = 48;

__device__ __forceinline__ void attn_store(const float (&o)[12], int rt, int warp, int lane, int head) {
    const float l0 = __shfl_sync(0xffffffff, o[8], (lane & ~3) | 2), l1 = __shfl_sync(0xffffffff, o[10], (lane & ~3) | 2);
    float r0, r1;
    asm("rcp.approx.ftz.f32 %0, %1;" : "=f"(r0) : "f"(l0));
    asm("rcp.approx.ftz.f32 %0, %1;" : "=f"(r1) : "f"(l1));
    const int row = rt * 64 + (warp & 3) * 16 + (lane >> 2);
    uint32_t* op = (uint32_t*)(g_o + (size_t)row * DM + head * HD) + (lane & 3);
    #pragma unroll
    for (int b = 0; b < 3; b++) {
        if (b < 2 || (lane & 3) < 2) {
            op[b * 4] = pack_bf16(o[b * 4] * r0, o[b * 4 + 1] * r0);
            op[b * 4 + 8 * DM / 2] = pack_bf16(o[b * 4 + 2] * r1, o[b * 4 + 3] * r1);
        }
    }
}
__device__ __forceinline__ void load_q(uint32_t (&d)[8], const uint32_t* qhead, int rt) {
    const uint32_t* p = qhead + (rt >> 1) * 1536 + (rt & 1) * 256;
    #pragma unroll
    for (int c = 0; c < 3; c++) {
        asm volatile("ld.global.cg.u32 %0, [%1];" : "=r"(d[c * 2]) : "l"(p + c * 512));
        asm volatile("ld.global.cg.u32 %0, [%1];" : "=r"(d[c * 2 + 1]) : "l"(p + c * 512 + 32));
    }
}
__device__ __forceinline__ void load_pad(uint32_t (&d)[8]) {
    asm volatile("ld.global.u32 %0, [%1];" : "=r"(d[6]) : "l"(g_zero));
    asm volatile("ld.global.u32 %0, [%1];" : "=r"(d[7]) : "l"(g_zero + 1));
}
__device__ __forceinline__ void attn_qk(float (&s)[32], const uint32_t (&q)[8], uint64_t k01, uint64_t k2) {
    wg_RS64_00(s, q[0], q[1], q[2], q[3], k01, 0);
    wg_RS64_00(s, q[4], q[5], q[6], q[7], k2, 1);
}

__device__ __forceinline__ void attn_qk(float (&s)[32], uint64_t q01, uint64_t q2, uint64_t k01, uint64_t k2) {
    wg_SS64_00(s, q01, k01, 0);
    wg_SS64_00(s, q2, k2, 1);
}

__device__ __forceinline__ void attn_fallback(const uint32_t* qhead, int head, int qblk, int warp, int lane, uint64_t dT) {
    #pragma unroll 1
    for (int t = warp >> 2; t < 8; t += 3) {
        uint32_t q[8];
        load_q(q, qhead, qblk * 8 + t);
        load_pad(q);
        if ((lane & 3) >= 2) { q[4] = 0; q[5] = 0; }
        asm volatile("" : "+r"(q[4]), "+r"(q[5]) :: "memory");
        float o[12], s[2][32];
        #pragma unroll
        for (int i = 0; i < 12; i++) o[i] = 0.f;
        pin(o);
        float m0 = -INFINITY, m1 = -INFINITY;
        uint64_t d = dT;
        #pragma unroll 1
        for (int j = 0; j < 16; j++) {
            wg_fence();
            attn_qk(s[0], q, d, d + D_K2);
            attn_qk(s[1], q, d + D_KB, d + D_K2 + D_K2B);
            wg_commit();
            wg_wait<0>();
            pin(s[0]); pin(s[1]);
            float x0 = m0, x1 = m1;
            #pragma unroll
            for (int b = 0; b < 16; b++) {
                const float* v = s[b >> 3] + (b & 7) * 4;
                x0 = fmaxf(x0, fmaxf(v[0], v[1])); x1 = fmaxf(x1, fmaxf(v[2], v[3]));
            }
            x0 = fmaxf(x0, __shfl_xor_sync(0xffffffff, x0, 1)); x0 = fmaxf(x0, __shfl_xor_sync(0xffffffff, x0, 2));
            x1 = fmaxf(x1, __shfl_xor_sync(0xffffffff, x1, 1)); x1 = fmaxf(x1, __shfl_xor_sync(0xffffffff, x1, 2));
            const float c0 = ex2(m0 - x0), c1 = ex2(m1 - x1);
            m0 = x0; m1 = x1;
            #pragma unroll
            for (int b = 0; b < 3; b++) { o[b * 4] *= c0; o[b * 4 + 1] *= c0; o[b * 4 + 2] *= c1; o[b * 4 + 3] *= c1; }
            pin(o);
            uint32_t p[32];
            #pragma unroll
            for (int b = 0; b < 16; b++) {
                const float* v = s[b >> 3] + (b & 7) * 4;
                p[b * 2] = pack_bf16(ex2(v[0] - m0), ex2(v[1] - m0));
                p[b * 2 + 1] = pack_bf16(ex2(v[2] - m1), ex2(v[3] - m1));
            }
            pin(p);
            wg_fence();
            #pragma unroll
            for (int kk = 0; kk < 8; kk++) wg_RS24_01(o, p[kk * 4], p[kk * 4 + 1], p[kk * 4 + 2], p[kk * 4 + 3], d + D_V + kk * D_VK, 1);
            wg_commit();
            wg_wait<0>();
            pin(o);
            d += D_TILE;
        }
        attn_store(o, qblk * 8 + t, warp, lane, head);
    }
}

__global__ void __launch_bounds__(384, 1)
k2_attn(const __nv_bfloat16* __restrict__ wo, const __nv_bfloat16* __restrict__ wg_, const __nv_bfloat16* __restrict__ wu, const __nv_bfloat16* __restrict__ wd,
        const uint32_t sh16, const bool placed) {
    extern __shared__ __align__(1024) uint8_t smem[];
    const uint32_t sb = opaque(smem_u32(smem));
    const int tid = threadIdx.x, lane = tid & 31;
    const int warp = __shfl_sync(0xffffffff, tid >> 5, 0);
    pdl_launch();
    if (blockIdx.x >= 128) {
        const int e = blockIdx.x - 128;
        const __nv_bfloat16* w = (e < 2 ? wg_ : wu);
        auto pull = [&](const void* base, uint32_t bytes) {
            for (uint32_t off = tid * 128; off < bytes; off += 384 * 128) asm volatile("prefetch.global.L2 [%0];" :: "l"((const uint8_t*)base + off));
        };
        pull(w + (size_t)(e & 1) * 320 * FF, 320 * FF * 2);
        pull(wo + (size_t)e * 160 * DM, 160 * DM * 2);
        pull(wd + (size_t)e * 432 * DM, 432 * DM * 2);
        if (e == 0 && warp == 11) {
            pdl_wait();
            const uint32_t tag = (__ldcg(&g_epoch) + 1) & 0xFFFFFFu;
            uint32_t next = 128;
            for (int sm = lane; sm < 160; sm += 32) {
                const uint32_t v = sm < NSM ? __ldcg(g_rank + sm) : 0;
                const bool free_sm = sm < NSM && (v >> 8) != tag;
                const uint32_t m = __ballot_sync(0xffffffff, free_sm);
                if (sm < NSM) g_place[sm] = free_sm ? (tag << 8) | (next + __popc(m & ((1u << lane) - 1))) : v;
                next += __popc(m);
            }
            if (next != NSM && placed) __trap();
        }
        float* red = (float*)smem;
        const int cgp = tid % 108, rg = tid / 108;
        if (rg < 3) {
            float c[8];
            #pragma unroll
            for (int j = 0; j < 8; j++) c[j] = 0.f;
            const uint4* p = (const uint4*)(w + (e & 1) * 864 + cgp * 8);
            uint4 v[2][12];
            auto ld = [&](uint4 (&d)[12], int r0) {
                #pragma unroll
                for (int i = 0; i < 12; i++) { const int r = r0 + i * 3; d[i] = r < DM ? __ldg(p + (size_t)r * (FF / 8)) : make_uint4(0, 0, 0, 0); }
            };
            auto add = [&](const uint4 (&d)[12]) {
                #pragma unroll
                for (int i = 0; i < 12; i++) {
                    c[0] += bf_lo(d[i].x); c[1] += bf_hi(d[i].x); c[2] += bf_lo(d[i].y); c[3] += bf_hi(d[i].y);
                    c[4] += bf_lo(d[i].z); c[5] += bf_hi(d[i].z); c[6] += bf_lo(d[i].w); c[7] += bf_hi(d[i].w);
                }
            };
            ld(v[0], rg);
            #pragma unroll 1
            for (int r0 = rg; r0 < DM; r0 += 72) {
                ld(v[1], r0 + 36); add(v[0]);
                ld(v[0], r0 + 72); add(v[1]);
            }
            #pragma unroll
            for (int j = 0; j < 8; j++) red[rg * 864 + cgp * 8 + j] = c[j];
        }
        __syncthreads();
        for (int i = tid; i < 864; i += 384) g_cs2[e * 864 + i] = red[i] + red[864 + i] + red[1728 + i];
        pdl_wait();
        if (e == 0 && tid == 0) g_epoch += 1;
        return;
    }
    const uint32_t sBar = sb + K2_BAR, sRed = sBar + 128;
    const int wg = warp >> 2;
    const int head = blockIdx.x >> 2, qblk = blockIdx.x & 3;
    if (warp == 0 && elect_one()) { mbar_init_n<1>(sBar, 2); mbar_init_n<1>(sBar + 8, 1); mbar_init_n<1>(sBar + 16, 2); }
    if (warp == 2 && elect_one()) mbar_init_n<6>(sBar + 24, 1);
    if (tid == 32) asm volatile("st.shared.v2.u32 [%0], {%1, %1};" :: "r"(sRed), "r"(0u) : "memory");
    if (wg == 1 && tid < 192) asm volatile("st.shared.v4.u32 [%0], {%1, %1, %1, %1};" :: "r"(sb + K2_ZERO + (tid - 128) * 16), "r"(0u) : "memory");
    proxy_fence();
    __syncthreads();
    pdl_wait();
    const uint8_t* const kvsrc = g_kv + (size_t)head * KV_HEAD;
    auto load_kv = [&](int bar, uint32_t off, uint32_t bytes) {
        if ((warp & 3) == 0 && elect_one()) {
            mbar_expect(sBar + bar * 8, bytes);
            bulk_g2s(sb + off, kvsrc + off, bytes, sBar + bar * 8);
        }
        __syncwarp();
    };
    auto load_qs = [&](int half) {
        if ((warp & 3) == 1 && elect_one()) {
            mbar_expect(sBar + half * 16, 12288);
            bulk_g2s(sb + K2_Q + half * 12288, g_q + (size_t)head * Q_HEAD + qblk * 24576 + half * 12288, 12288, sBar + half * 16);
        }
        __syncwarp();
    };
    if (wg == 0) { load_kv(0, 0, 6144); load_qs(0); }
    if (wg == 1) load_kv(1, 6144, 6144 + 2 * 12288);
    auto q_desc = [&](int t, uint64_t& a, uint64_t& b) {
        const uint32_t base = K2_Q + (t >> 1) * 6144 + (t & 1) * 1024;
        a = mkdesc(sb + base, 2048, 128, 0);
        b = mkdesc(sb + base + 4096, K2_ZERO - base - 4096, 128, 0);
    };
    uint64_t qa, qb;
    q_desc(wg, qa, qb);
    const uint64_t dT = mkdesc(sb, 128, 256, 0);
    auto note_max = [&](uint32_t v, uint32_t slot) {
        v = __reduce_max_sync(0xffffffff, v);
        if (elect_one()) asm volatile("red.shared.max.u32 [%0], %1;" :: "r"(sRed + slot), "r"(v) : "memory");
        __syncwarp();
    };
    auto row_norm = [&](uint32_t a0, uint32_t a1, uint32_t a2) {
        const uint4 u = lds128(a0), v = lds128(a1), w = lds128(a2);
        const uint32_t e[10] = {u.x, u.y, u.z, u.w, v.x, v.y, v.z, v.w, w.x, w.y};
        uint32_t n0, n1;
        asm("mul.rn.bf16x2 %0, %1, %1;" : "=r"(n0) : "r"(e[0]));
        asm("mul.rn.bf16x2 %0, %1, %1;" : "=r"(n1) : "r"(e[1]));
        #pragma unroll
        for (int i = 2; i < 10; i += 2) {
            asm("fma.rn.bf16x2 %0, %1, %1, %0;" : "+r"(n0) : "r"(e[i]));
            asm("fma.rn.bf16x2 %0, %1, %1, %0;" : "+r"(n1) : "r"(e[i + 1]));
        }
        asm("add.rn.bf16x2 %0, %0, %1;" : "+r"(n0) : "r"(n1));
        return __float_as_uint(bf_lo(n0) + __uint_as_float(n0)) & 0x7FFFFFFFu;
    };
    float o[12], sa[32], sc[32];
    uint32_t pa[16], pc[16];
    auto softmax_pv = [&](float (&s)[32], uint32_t (&p)[16], uint64_t v) {
        #pragma unroll
        for (int b = 0; b < 8; b++) {
            if ((MUFU_MASK >> b) & 1) {
                p[b * 2] = pack_bf16(ex2(s[b * 4]), ex2(s[b * 4 + 1]));
                p[b * 2 + 1] = pack_bf16(ex2(s[b * 4 + 2]), ex2(s[b * 4 + 3]));
            } else {
                p[b * 2] = exp2_pair(s[b * 4], s[b * 4 + 1], sh16);
                p[b * 2 + 1] = exp2_pair(s[b * 4 + 2], s[b * 4 + 3], sh16);
            }
        }
        pin(p);
        wg_fence();
        #pragma unroll
        for (int kk = 0; kk < 4; kk++) wg_RS24_01(o, p[kk * 4], p[kk * 4 + 1], p[kk * 4 + 2], p[kk * 4 + 3], v + kk * D_VK, 1);
    };
    #pragma unroll
    for (int i = 0; i < 12; i++) o[i] = 0.f;
    pin(o);
    mbar_wait(sBar, 0);
    wg_fence();
    attn_qk(sa, qa, qb, dT, dT + D_K2);
    attn_qk(sc, qa, qb, dT + D_KB, dT + D_K2 + D_K2B);
    wg_commit();
    if (wg == 2) { load_kv(2, 3 * 12288, 2 * 12288); load_qs(1); }
    wg_wait<0>(); pin(sa); pin(sc);
    const int njobs = wg == 1 ? 4 : 3;
    uint32_t dlo = (uint32_t)dT + 1;
    int turn = wg;
    #pragma unroll 1
    for (int job = 0; job < njobs; job++) {
        const int t = job < 2 ? wg + 3 * job : (wg == 0 || (wg == 1 && job == 2)) ? 6 : 7;
        int left = job < 2 ? 15 : wg == 0 ? 10 : wg == 1 ? (job == 2 ? 4 : 5) : 9, seg = 1;
        #pragma unroll 1
        do {
            int n = left;
            if (job == 0) {
                mbar_wait(sBar + 8 * seg, 0);
                if (turn == 0) {
                    if (seg < 7) load_kv(seg + 2, (2 * seg + 3) * 12288, seg < 6 ? 2 * 12288 : 12288);
                    const uint32_t ti = opaque(threadIdx.x), kb = sb + seg * 24576 + (ti & 7) * 16;
                    const uint32_t kn0 = kb + (ti & 120) * 32, kn1 = kb + 4096 + (ti & 56) * 32 + (ti & 64) * 2;
                    note_max(max(row_norm(kn0 - 24576, kn0 - 24576 + 128, kn1 - 24576), row_norm(kn0 - 12288, kn0 - 12288 + 128, kn1 - 12288)), 0);
                    turn = 3;
                }
                turn--; n = seg < 8 ? 2 : 1; seg++;
            }
            left -= n;
            const uint32_t dend = dlo + n * (uint32_t)D_TILE;
            #pragma unroll 1
            do {
                uint64_t d;
                asm("mov.b64 %0, {%1, %2};" : "=l"(d) : "r"(dlo), "r"(16u));
                wg_wait<1>(); pin(sa);
                softmax_pv(sa, pa, d + (D_V - 1));
                attn_qk(sa, qa, qb, d + (D_TILE - 1), d + (D_TILE + D_K2 - 1));
                wg_commit(); wg_wait<1>(); pin(sc);
                softmax_pv(sc, pc, d + (D_V + 4 * D_VK - 1));
                attn_qk(sc, qa, qb, d + (D_TILE + D_KB - 1), d + (D_TILE + D_K2 + D_K2B - 1));
                wg_commit();
                dlo += (uint32_t)D_TILE;
            } while (dlo != dend);
        } while (left);
        wg_wait<1>(); pin(sa);
        uint64_t d;
        asm volatile("mov.b64 %0, {%1, %2};" : "=l"(d) : "r"(dlo), "r"(16u));
        const int jn = job + 1;
        const uint64_t dn = dT + (jn < 2 ? 0 : wg == 0 ? 0 : wg == 1 ? (jn == 2 ? 11 : 0) : 6) * D_TILE;
        q_desc(jn < 2 ? wg + 3 : (wg == 0 || (wg == 1 && jn == 2)) ? 6 : 7, qa, qb);
        softmax_pv(sa, pa, d + (D_V - 1));
        attn_qk(sa, qa, qb, dn, dn + D_K2);
        wg_commit(); wg_wait<1>(); pin(sc);
        softmax_pv(sc, pc, d + (D_V + 4 * D_VK - 1));
        attn_qk(sc, qa, qb, dn + D_KB, dn + D_K2 + D_K2B);
        wg_commit();
        dlo = (uint32_t)dn + 1;
        wg_wait<0>(); pin(sa); pin(sc);
        float of[12];
        #pragma unroll
        for (int i = 0; i < 12; i++) asm volatile("mov.b32 %0, %1;" : "=f"(of[i]) : "f"(o[i]));
        #pragma unroll
        for (int i = 0; i < 12; i++) o[i] = 0.f;
        pin(o);
        if (job == 0) {
            const uint32_t a = sb + K2_Q + (opaque(threadIdx.x) & 127) * 16;
            uint32_t v = row_norm(a + wg * 6144, a + wg * 6144 + 2048, a + wg * 6144 + 4096);
            if (wg == 0) v = max(v, row_norm(a + 3 * 6144, a + 3 * 6144 + 2048, a + 3 * 6144 + 4096));
            note_max(v, 4);
            if (wg == 0) bar_arrive(3, 256);
        }
        if (job >= 2) {
            if (wg == 1) {
                if (job == 3) bar_sync(3, 256);
                const uint32_t a = sb + (job == 2 ? K2_X : K2_Q) + (tid & 127) * 16;
                #pragma unroll
                for (int i = 0; i < 3; i++)
                    asm volatile("st.shared.v4.f32 [%0], {%1,%2,%3,%4};" :: "r"(a + i * 2048), "f"(of[i * 4]), "f"(of[i * 4 + 1]), "f"(of[i * 4 + 2]), "f"(of[i * 4 + 3]) : "memory");
                bar_arrive(job - 1, 256);
                continue;
            }
            bar_sync(wg == 0 ? 1 : 2, 256);
            const uint32_t a = sb + (wg == 0 ? K2_X : K2_Q) + (tid & 127) * 16;
            #pragma unroll
            for (int i = 0; i < 3; i++) {
                const uint4 v = lds128(a + i * 2048);
                of[i * 4] += __uint_as_float(v.x); of[i * 4 + 1] += __uint_as_float(v.y); of[i * 4 + 2] += __uint_as_float(v.z); of[i * 4 + 3] += __uint_as_float(v.w);
            }
        }
        {
            float z = 0.f;
            #pragma unroll
            for (int i = 0; i < 12; i++) z = fmaf(of[i], 0.f, z);
            if (z != 0.f) asm volatile("red.shared.max.u32 [%0], %1;" :: "r"(sRed + 4), "r"(0x7FFFFFFFu) : "memory");
        }
        attn_store(of, qblk * 8 + t, warp, lane, head);
    }
    __syncthreads();
    uint32_t km, qm;
    asm volatile("ld.shared.v2.u32 {%0,%1}, [%2];" : "=r"(km), "=r"(qm) : "r"(sRed) : "memory");
    if (!(__uint_as_float(km) * __uint_as_float(qm) * 1.1f <= SAFE_S * SAFE_S))
        attn_fallback((const uint32_t*)(g_q + (size_t)head * Q_HEAD) + (warp & 3) * 64 + lane, head, qblk, warp, lane, dT);
}

__device__ __forceinline__ uint32_t resid_addr(uint32_t sTile, int warp, int lane) {
    const int t = (lane >> 4) * 8 + (lane & 7), chunk = (warp & 3) * 2 + ((lane >> 3) & 1);
    return sTile + t * 128 + ((chunk ^ (t & 7)) << 4);
}
__device__ __forceinline__ void resid_load(uint32_t (&r)[20], uint32_t a) {
    #pragma unroll
    for (int b = 0; b < 5; b++) ldsm_x4_t(a + b * 2048, r[b * 4], r[b * 4 + 1], r[b * 4 + 2], r[b * 4 + 3]);
}
template<bool SCALE>
__device__ __forceinline__ void resid_store(const float (&acc)[40], const uint32_t (&r)[20], const float2 (&sc)[10], uint32_t a) {
    #pragma unroll
    for (int b = 0; b < 5; b++) {
        uint32_t o[4];
        #pragma unroll
        for (int i = 0; i < 4; i++) {
            const float2 f = SCALE ? sc[b * 2 + (i >> 1)] : make_float2(1.f, 1.f);
            o[i] = pack_bf16(fmaf(acc[b * 8 + i * 2], f.x, bf_lo(r[b * 4 + i])), fmaf(acc[b * 8 + i * 2 + 1], f.y, bf_hi(r[b * 4 + i])));
        }
        stsm_x4_t(a + b * 2048, o[0], o[1], o[2], o[3]);
    }
}

constexpr int K3_NO = 6;
constexpr int K3_SMEM = 10 * 16384 + K3_NO * 10240 + 256;

__global__ void __launch_bounds__(352, 1)
k3_wo(const __grid_constant__ CUtensorMap tmWo, const __grid_constant__ CUtensorMap tmO, const __grid_constant__ CUtensorMap tmXr, const __grid_constant__ CUtensorMap tmH,
      const bool placed) {
    extern __shared__ __align__(1024) uint8_t smem[];
    const uint32_t sb = opaque(smem_u32(smem));
    const uint32_t sW = sb, sO = sW + 10 * 16384, sR = sW, sFull = sO + K3_NO * 10240, sEmpty = sFull + 80, sRes = sEmpty + 32;
    const int tid = threadIdx.x, lane = tid & 31;
    const int warp = __shfl_sync(0xffffffff, tid >> 5, 0);
    uint32_t entry = place_entry(placed);
    if (warp == 0 && elect_one()) mbar_init_n<7>(sFull, 2);
    if (warp == 1 && elect_one()) mbar_init_n<7>(sFull + 56, 2);
    if (warp == 2 && elect_one()) { mbar_init_n<1>(sRes, 1); tmap_prefetch(&tmXr); tmap_prefetch(&tmH); }
    if (warp == 3 && elect_one()) { tmap_prefetch(&tmWo); tmap_prefetch(&tmO); }
    entry = __shfl_sync(0xffffffff, entry, 0);
    const int tile = entry & 255, cg = tile % 5, tb = tile / 5;
    if (warp == 10 || tile >= 130) {
        pdl_launch();
        if (tid == 320 && placed) place_guard(g_started, entry);
        return;
    }
    bar_sync(15, 320);
    pdl_launch();
    if (warp == 8) {
        pdl_wait();
        if (elect_one()) {
            #pragma unroll 1
            for (int kb = 0; kb < 10; kb++) {
                mbar_expect(sFull + kb * 8, 16384);
                tma_load(sW + kb * 16384, &tmWo, sFull + kb * 8, cg * 128, kb * 64);
                tma_load(sW + kb * 16384 + 8192, &tmWo, sFull + kb * 8, cg * 128 + 64, kb * 64);
            }
        }
        __syncwarp();
        mbar_wait(sEmpty, 0);
        mbar_wait(sEmpty + 8, 0);
        if (elect_one()) {
            mbar_expect(sRes, 20480);
            tma_load(sR, &tmXr, sRes, cg * 128, tb * 80);
            tma_load(sR + 10240, &tmXr, sRes, cg * 128 + 64, tb * 80);
        }
    } else if (warp == 9) {
        pdl_wait();
        #pragma unroll 1
        for (int kb = 0; kb < 10; kb++) {
            const int sl = kb < K3_NO ? kb : kb - K3_NO;
            if (kb >= K3_NO) mbar_wait(sEmpty + sl * 8, 0);
            if (elect_one()) {
                mbar_expect(sFull + kb * 8, 10240);
                tma_load(sO + sl * 10240, &tmO, sFull + kb * 8, kb * 64, tb * 80);
            }
            __syncwarp();
        }
    } else {
        const int wg = warp >> 2;
        float acc[40];
        const uint64_t dA = mkdesc(sW + wg * 8192, 8192, 1024, 1), dB = mkdesc(sO, 16, 1024, 1);
        #pragma unroll
        for (int kb = 0; kb < 10; kb++) {
            mbar_wait(sFull + kb * 8, 0);
            wg_fence();
            #pragma unroll
            for (int k = 0; k < 4; k++) wg_SS80_10(acc, dA + kb * 1024 + k * 128, dB + (kb % K3_NO) * 640 + k * 2, (kb | k) ? 1 : 0);
            wg_commit();
            if (kb >= 1 && kb <= 4) { wg_wait<1>(); if ((tid & 127) == 0) mbar_arrive(sEmpty + (kb - 1) * 8); }
        }
        uint32_t res[20];
        float2 one[10];
        const uint32_t ra = resid_addr(sR + wg * 10240, warp, lane);
        mbar_wait(sRes, 0);
        resid_load(res, ra);
        wg_wait<0>();
        pin(acc);
        resid_store<false>(acc, res, one, ra);
        proxy_fence();
        bar_sync(1 + wg, 128);
        if ((tid & 127) == 0) {
            tma_store(&tmH, sR + wg * 10240, cg * 128 + wg * 64, tb * 80);
            tma_store_commit_wait();
        }
        if ((tid & 127) >= 32 && (tid & 127) < 112) {
            const int t = (tid & 127) - 32;
            const uint32_t a = sR + wg * 10240 + t * 128;
            float v[64];
            #pragma unroll
            for (int c = 0; c < 8; c++) {
                const uint4 w = lds128(a + ((c ^ (t & 7)) << 4));
                v[c * 8] = bf_lo(w.x); v[c * 8 + 1] = bf_hi(w.x); v[c * 8 + 2] = bf_lo(w.y); v[c * 8 + 3] = bf_hi(w.y);
                v[c * 8 + 4] = bf_lo(w.z); v[c * 8 + 5] = bf_hi(w.z); v[c * 8 + 6] = bf_lo(w.w); v[c * 8 + 7] = bf_hi(w.w);
            }
            float s0 = 0.f, s1 = 0.f, s2 = 0.f, s3 = 0.f;
            #pragma unroll
            for (int i = 0; i < 64; i += 4) { s0 += v[i]; s1 += v[i + 1]; s2 += v[i + 2]; s3 += v[i + 3]; }
            const float s = (s0 + s1) + (s2 + s3), mean = s * (1.f / 64.f);
            s0 = s1 = s2 = s3 = 0.f;
            #pragma unroll
            for (int i = 0; i < 64; i += 4) {
                const float d0 = v[i] - mean, d1 = v[i + 1] - mean, d2 = v[i + 2] - mean, d3 = v[i + 3] - mean;
                s0 = fmaf(d0, d0, s0); s1 = fmaf(d1, d1, s1); s2 = fmaf(d2, d2, s2); s3 = fmaf(d3, d3, s3);
            }
            g_st2[(cg * 2 + wg) * 2080 + tb * 80 + t] = make_float2(s, (s0 + s1) + (s2 + s3));
        }
    }
}

constexpr int K4_NST = 4;
constexpr int K4_SMEM = 10 * 16384 + K4_NST * 16384 + 256 + 1024 + 1792;

template<int NB>
__device__ __forceinline__ void glu_store(const float (&a0)[NB * 8], const float (&a1)[NB * 8], const uint8_t* smem, int mb, int fs, int col0) {
    const int t = opaque(threadIdx.x), lane = t & 31, rloc = ((t >> 5) & 3) * 16 + (lane >> 2), row = mb * 128 + rloc;
    const float* const st = (const float*)(smem + (10 + K4_NST) * 16384 + 256) + rloc;
    const float* const cs = (const float*)(smem + (10 + K4_NST) * 16384 + 256 + 1024) + (lane & 3) * 2 - fs * 224 + col0;
    float mean[4];
    #pragma unroll
    for (int h = 0; h < 4; h++) mean[h] = st[(h >> 1) * 64 + (h & 1) * 8];
    #pragma unroll
    for (int g4 = 0; g4 < NB; g4 += 4) {
        uint32_t p[4][4];
        #pragma unroll
        for (int jj = 0; jj < 4; jj++) {
            const int j = g4 + jj;
            const float2 cgv = *(const float2*)(cs + j * 8), cuv = *(const float2*)(cs + 224 + j * 8);
            #pragma unroll
            for (int h = 0; h < 4; h++) {
                const float* g = (h < 2 ? a0 : a1) + j * 4 + (h & 1) * 2;
                const float* u = g + NB * 4;
                p[h][jj] = pack_bf16((g[0] - mean[h] * cgv.x) * (u[0] - mean[h] * cuv.x), (g[1] - mean[h] * cgv.y) * (u[1] - mean[h] * cuv.y));
            }
        }
        #pragma unroll
        for (int h = 0; h < 4; h++)
            *(uint4*)(g_hh + (size_t)(row + (h >> 1) * 64 + (h & 1) * 8) * FF + col0 + g4 * 8 + (lane & 3) * 8) = make_uint4(p[h][0], p[h][1], p[h][2], p[h][3]);
    }
}

__global__ void __launch_bounds__(384, 1)
k4_glu(const __grid_constant__ CUtensorMap tmH, const __grid_constant__ CUtensorMap tmG64, const __grid_constant__ CUtensorMap tmU64,
       const __grid_constant__ CUtensorMap tmG32, const __grid_constant__ CUtensorMap tmU32) {
    extern __shared__ __align__(1024) uint8_t smem[];
    const uint32_t sb = opaque(smem_u32(smem));
    const uint32_t sA = sb, sB = sb + 10 * 16384, sAf = sB + K4_NST * 16384, sFull = sAf + 80, sEmpty = sFull + 32;
    const int tid = threadIdx.x;
    const int warp = __shfl_sync(0xffffffff, tid >> 5, 0);
    const int mb = blockIdx.x >> 3, fs = blockIdx.x & 7;
    const int nfull = fs == 7 ? 2 : 3;
    const int full0 = fs * 224 + ((fs & 1) ? 32 : 0), half0 = fs * 224 + ((fs & 1) ? 0 : 192);
    if (warp == 0 && elect_one()) mbar_init_n<5>(sAf, 1);
    if (warp == 1 && elect_one()) mbar_init_n<5>(sAf + 40, 1);
    if (warp == 2 && elect_one()) mbar_init_n<K4_NST>(sFull, 2);
    if (warp == 3 && elect_one()) mbar_init_n<K4_NST>(sEmpty, 1);
    if (warp == 4 && elect_one()) { tmap_prefetch(&tmH); tmap_prefetch(&tmG64); tmap_prefetch(&tmU64); }
    if (warp == 5 && elect_one()) { tmap_prefetch(&tmG32); tmap_prefetch(&tmU32); }
    __syncthreads();
    pdl_launch();
    if (warp >= 8) {
        asm volatile("setmaxnreg.dec.sync.aligned.u32 40;");
        if (warp > 9) {
            pdl_wait();
            if (warp == 10) {
                #pragma unroll 1
                for (int i = 0; i < 10; i++) {
                    if (i == 2) bar_sync(5, 96);
                    if (elect_one()) { mbar_expect(sAf + i * 8, 16384); tma_load(sA + i * 16384, &tmH, sAf + i * 8, i * 64, mb * 128); }
                    __syncwarp();
                }
            }
            float* const scs = (float*)(smem + (10 + K4_NST) * 16384 + 256 + 1024);
            #pragma unroll
            for (int i = tid - 320; i < 112; i += 64) {
                const int c = (i < 56 ? i : i - 56) * 4;
                ((float4*)scs)[i] = fs * 224 + c < FF ? __ldcg((const float4*)(g_cs2 + (i < 56 ? 0 : FF) + fs * 224 + c)) : make_float4(0.f, 0.f, 0.f, 0.f);
            }
            #pragma unroll 1
            for (int r = tid - 320; r < 128; r += 64) {
                float2 v[10];
                float m = 0.f, q = 0.f;
                #pragma unroll
                for (int c = 0; c < 10; c++) v[c] = __ldcg(g_st2 + c * 2080 + mb * 128 + r);
                #pragma unroll
                for (int c = 0; c < 10; c++) m += v[c].x;
                m *= (1.f / DM);
                #pragma unroll
                for (int c = 0; c < 10; c++) { const float d = v[c].x * (1.f / 64.f) - m; q += v[c].y + 64.f * d * d; }
                ((float*)(smem + (10 + K4_NST) * 16384 + 256))[r] = m;
                if (fs == 0) g_rs2[mb * 128 + r] = 1.f / (q * (1.f / DM) + LN_EPS);
            }
            bar_arrive(3, 192);
            bar_arrive(4, 192);
            return;
        }
        pdl_wait();
        const int nsteps = nfull * 10 + 5, up = warp - 8;
        int unit = 0, kb = 0;
        #pragma unroll 1
        for (int s = 0; s < nsteps; s++) {
            const int st = s & 3;
            if (s >= K4_NST) mbar_wait(sEmpty + st * 8, ((s >> 2) & 1) ^ 1);
            if (elect_one()) {
                const uint32_t base = sB + st * 16384, bar = sFull + st * 8;
                if (unit < nfull) {
                    mbar_expect(bar, 8192);
                    if (up) tma_load(base + 8192, &tmU64, bar, full0 + unit * 64, kb * 64);
                    else tma_load(base, &tmG64, bar, full0 + unit * 64, kb * 64);
                } else {
                    mbar_expect(bar, 8192);
                    if (up) tma_load(base + 8192, &tmU32, bar, half0, kb * 128);
                    else tma_load(base, &tmG32, bar, half0, kb * 128);
                }
            }
            __syncwarp();
            if (s == K4_NST - 1) bar_arrive(5, 96);
            if (++kb == 10) { kb = 0; unit++; }
        }
    } else {
        asm volatile("setmaxnreg.inc.sync.aligned.u32 232;");
        const int wg = warp >> 2;
        const uint64_t dA = mkdesc(sA, 16, 1024, 1), dB = mkdesc(sB, 8192, 1024, 1), dBh = mkdesc(sB, 8192, 512, 2);
        #pragma unroll 1
        for (int unit = wg; unit < nfull; unit += 2) {
            const int s0 = unit * 10;
            {
                float a0[64], a1[64];
                if (unit > 0) bar_sync(1 + wg, 256);
                #pragma unroll 1
                for (int kb = 0; kb < 10; kb++) {
                    const int s = s0 + kb, st = s & 3;
                    if (unit < 2) mbar_wait(sAf + kb * 8, 0);
                    mbar_wait(sFull + st * 8, (s >> 2) & 1);
                    if (kb == 9) bar_arrive(2 - wg, 256);
                    wg_fence();
                    const uint64_t da = dA + (uint64_t)(kb * 1024), db = dB + (uint64_t)(st * 1024);
                    #pragma unroll
                    for (int k = 0; k < 4; k++) {
                        wg_SS128_01(a0, da + k * 2, db + k * 128, k > 0 ? 1 : kb);
                        wg_SS128_01(a1, da + 512 + k * 2, db + k * 128, k > 0 ? 1 : kb);
                    }
                    wg_commit();
                    wg_wait<1>();
                    if (kb > 0 && (tid & 127) == 0) mbar_arrive(sEmpty + ((s - 1) & 3) * 8);
                }
                wg_wait<0>();
                pin(a0); pin(a1);
                if ((tid & 127) == 0) mbar_arrive(sEmpty + ((s0 + 9) & 3) * 8);
                if (unit < 2) bar_sync(3 + wg, 192);
                glu_store<8>(a0, a1, smem, mb, fs, full0 + unit * 64);
            }
        }
        if (wg == (nfull & 1)) {
            const int s0 = nfull * 10;
            {
                float a0[32], a1[32];
                bar_sync(1 + wg, 256);
                #pragma unroll 1
                for (int kb = 0; kb < 5; kb++) {
                    const int s = s0 + kb, st = s & 3;
                    mbar_wait(sFull + st * 8, (s >> 2) & 1);
                    wg_fence();
                    const uint64_t da = dA + (uint64_t)(kb * 2048), db = dBh + (uint64_t)(st * 1024);
                    #pragma unroll
                    for (int k = 0; k < 8; k++) {
                        wg_SS64_01(a0, da + (k >> 2) * 1024 + (k & 3) * 2, db + k * 64, k > 0 ? 1 : kb);
                        wg_SS64_01(a1, da + (k >> 2) * 1024 + 512 + (k & 3) * 2, db + k * 64, k > 0 ? 1 : kb);
                    }
                    wg_commit();
                    if (kb == 1) { wg_wait<1>(); if ((tid & 127) == 0) mbar_arrive(sEmpty + ((s - 1) & 3) * 8); }
                }
                wg_wait<0>();
                pin(a0); pin(a1);
                glu_store<4>(a0, a1, smem, mb, fs, half0);
            }
        }
    }
}

constexpr int K5_NW = 6, K5_NH = 10;
constexpr int K5_SMEM = K5_NW * 16384 + K5_NH * 10240 + 2 * 10240 + 512 + 320;

__global__ void __launch_bounds__(352, 1)
k5_down(const __grid_constant__ CUtensorMap tmWd, const __grid_constant__ CUtensorMap tmHH, const __grid_constant__ CUtensorMap tmHr, const __grid_constant__ CUtensorMap tmOut,
        const bool placed) {
    extern __shared__ __align__(1024) uint8_t smem[];
    const uint32_t sb = opaque(smem_u32(smem));
    const uint32_t sH = sb + K5_NW * 16384, sR = sH + K5_NH * 10240, sFw = sR + 2 * 10240, sEw = sFw + 96, sFh = sEw + 96, sEh = sFh + 96, sRes = sEh + 96;
    const uint32_t sS = sR + 2 * 10240 + 512;
    const int tid = threadIdx.x, lane = tid & 31;
    const int warp = __shfl_sync(0xffffffff, tid >> 5, 0);
    uint32_t entry = place_entry(placed);
    if (warp == 0 && elect_one()) mbar_init_n<K5_NW>(sFw, 1);
    if (warp == 1 && elect_one()) mbar_init_n<K5_NW>(sEw, 2);
    if (warp == 2 && elect_one()) mbar_init_n<K5_NH>(sFh, 1);
    if (warp == 3 && elect_one()) mbar_init_n<K5_NH>(sEh, 2);
    if (warp == 4 && elect_one()) { mbar_init_n<1>(sRes, 1); tmap_prefetch(&tmHr); tmap_prefetch(&tmOut); }
    if (warp == 5 && elect_one()) { tmap_prefetch(&tmWd); tmap_prefetch(&tmHH); }
    entry = __shfl_sync(0xffffffff, entry, 0);
    const int tile = entry & 255, cg = tile % 5, row0 = (tile / 5) * 80;
    if (warp == 10 || tile >= 130) {
        if (tid == 320 && placed) place_guard(g_started + 1, entry);
        return;
    }
    bar_sync(15, 320);
    if (warp == 8) {
        pdl_wait();
        int st = 0, ph = 1;
        #pragma unroll 1
        for (int s = 0; s < 27; s++) {
            if (s >= K5_NW) mbar_wait(sEw + st * 8, ph);
            if (elect_one()) {
                mbar_expect(sFw + st * 8, 16384);
                tma_load5(sb + st * 16384, &tmWd, sFw + st * 8, cg * 128, s * 2);
                tma_load5(sb + st * 16384 + 8192, &tmWd, sFw + st * 8, cg * 128 + 64, s * 2);
            }
            __syncwarp();
            if (++st == K5_NW) { st = 0; ph ^= 1; }
        }
    } else if (warp == 9) {
        pdl_wait();
        int st = 0, ph = 1;
        #pragma unroll 1
        for (int s = 0; s < 27; s++) {
            if (s >= K5_NH) mbar_wait(sEh + st * 8, ph);
            if (elect_one()) {
                mbar_expect(sFh + st * 8, 10240);
                tma_load(sH + st * 10240, &tmHH, sFh + st * 8, s * 64, row0);
                if (s == 20) {
                    mbar_expect(sRes, 20480 + 320);
                    bulk_g2s(sS, g_rs2 + row0, 320, sRes);
                    tma_load(sR, &tmHr, sRes, cg * 128, row0);
                    tma_load(sR + 10240, &tmHr, sRes, cg * 128 + 64, row0);
                }
            }
            __syncwarp();
            if (++st == K5_NH) { st = 0; ph ^= 1; }
        }
    } else {
        const int wg = warp >> 2;
        float acc[40];
        const uint64_t dA = mkdesc(sb + wg * 8192, 8192, 1024, 1), dB = mkdesc(sH, 16, 1024, 1);
        int sw = 0, pw = 0, sh = 0, phh = 0, psw = 0, psh = 0;
        #pragma unroll 1
        for (int s = 0; s < 27; s++) {
            mbar_wait(sFw + sw * 8, pw);
            mbar_wait(sFh + sh * 8, phh);
            wg_fence();
            #pragma unroll
            for (int k = 0; k < 4; k++) wg_SS80_10(acc, dA + (uint64_t)(sw * 1024) + k * 128, dB + (uint64_t)(sh * 640) + k * 2, k > 0 ? 1 : s);
            wg_commit();
            wg_wait<1>();
            if (s > 0) {
                if ((tid & 127) == 0) mbar_arrive(sEh + psh * 8);
                if ((tid & 127) == 32) mbar_arrive(sEw + psw * 8);
            }
            psw = sw; psh = sh;
            if (++sw == K5_NW) { sw = 0; pw ^= 1; }
            if (++sh == K5_NH) { sh = 0; phh ^= 1; }
        }
        uint32_t res[20];
        float2 sc[10];
        const uint32_t ra = resid_addr(sR + wg * 10240, warp, lane);
        mbar_wait(sRes, 0);
        resid_load(res, ra);
        #pragma unroll
        for (int b = 0; b < 10; b++) asm volatile("ld.shared.v2.f32 {%0,%1}, [%2];" : "=f"(sc[b].x), "=f"(sc[b].y) : "r"(sS + b * 32 + (lane & 3) * 8) : "memory");
        wg_wait<0>();
        pin(acc);
        resid_store<true>(acc, res, sc, ra);
        proxy_fence();
        bar_sync(1 + wg, 128);
        if ((tid & 127) == 0) {
            tma_store(&tmOut, sR + wg * 10240, cg * 128 + wg * 64, row0);
            tma_store_commit_wait();
        }
    }
}

typedef CUresult (*EncodeFn)(CUtensorMap*, CUtensorMapDataType, cuuint32_t, void*, const cuuint64_t*, const cuuint64_t*, const cuuint32_t*,
                             const cuuint32_t*, CUtensorMapInterleave, CUtensorMapSwizzle, CUtensorMapL2promotion, CUtensorMapFloatOOBfill);

CUtensorMap make_map(EncodeFn enc, const void* p, int cols, int rows, int bc, int br) {
    CUtensorMap tm;
    cuuint64_t gd[2] = {(cuuint64_t)cols, (cuuint64_t)rows};
    cuuint64_t gs[1] = {(cuuint64_t)cols * 2};
    cuuint32_t box[2] = {(cuuint32_t)bc, (cuuint32_t)br}, es[2] = {1, 1};
    enc(&tm, CU_TENSOR_MAP_DATA_TYPE_BFLOAT16, 2, const_cast<void*>(p), gd, gs, box, es, CU_TENSOR_MAP_INTERLEAVE_NONE,
        bc == 64 ? CU_TENSOR_MAP_SWIZZLE_128B : CU_TENSOR_MAP_SWIZZLE_64B, CU_TENSOR_MAP_L2_PROMOTION_L2_256B, CU_TENSOR_MAP_FLOAT_OOB_FILL_NONE);
    return tm;
}

CUtensorMap make_map_perm(EncodeFn enc, const void* p, int nb) {
    CUtensorMap tm;
    cuuint64_t gd[5] = {(cuuint64_t)DM, 2, (cuuint64_t)nb, 4, (cuuint64_t)(FF / (8 * nb))};
    cuuint64_t gs[4] = {DM * 2, 8 * DM * 2, 2 * DM * 2, (cuuint64_t)nb * 8 * DM * 2};
    cuuint32_t box[5] = {64, 2, (cuuint32_t)nb, 4, (cuuint32_t)(8 / nb)}, es[5] = {1, 1, 1, 1, 1};
    enc(&tm, CU_TENSOR_MAP_DATA_TYPE_BFLOAT16, 5, const_cast<void*>(p), gd, gs, box, es, CU_TENSOR_MAP_INTERLEAVE_NONE,
        CU_TENSOR_MAP_SWIZZLE_128B, CU_TENSOR_MAP_L2_PROMOTION_L2_256B, CU_TENSOR_MAP_FLOAT_OOB_FILL_NONE);
    return tm;
}

template<typename... KArgs, typename... Args>
void launch(void (*kern)(KArgs...), int grid, int block, int smem, bool pdl, Args... args) {
    cudaLaunchConfig_t cfg = {};
    cfg.gridDim = dim3(grid); cfg.blockDim = dim3(block); cfg.dynamicSmemBytes = smem; cfg.stream = cudaStreamPerThread;
    cudaLaunchAttribute at[1];
    at[0].id = cudaLaunchAttributeProgrammaticStreamSerialization;
    at[0].val.programmaticStreamSerializationAllowed = 1;
    cfg.attrs = at; cfg.numAttrs = pdl ? 1 : 0;
    cudaLaunchKernelEx(&cfg, kern, args...);
}

}

extern "C" void kernel_launch(void* const* d_in, const int* in_sizes, int n_in, void* d_out, int out_size) {
    (void)in_sizes; (void)n_in; (void)out_size;
    const __nv_bfloat16* x = (const __nv_bfloat16*)d_in[0];
    const __nv_bfloat16* wqkv = (const __nv_bfloat16*)d_in[1];
    const __nv_bfloat16* wo = (const __nv_bfloat16*)d_in[2];
    const __nv_bfloat16* wg = (const __nv_bfloat16*)d_in[4];
    const __nv_bfloat16* wu = (const __nv_bfloat16*)d_in[5];
    const __nv_bfloat16* wd = (const __nv_bfloat16*)d_in[6];
    static EncodeFn enc = nullptr;
    static bool placed = false;
    if (!enc) {
        int nsm = 0;
        cudaDeviceGetAttribute(&nsm, cudaDevAttrMultiProcessorCount, 0);
        placed = nsm == NSM;
        void* fn = nullptr;
        cudaDriverEntryPointQueryResult qr;
        cudaGetDriverEntryPoint("cuTensorMapEncodeTiled", &fn, cudaEnableDefault, &qr);
        enc = (EncodeFn)fn;
        cudaFuncSetAttribute(k1_qkv, cudaFuncAttributeMaxDynamicSharedMemorySize, K1_SMEM);
        cudaFuncSetAttribute(k2_attn, cudaFuncAttributeMaxDynamicSharedMemorySize, K2_SMEM);
        cudaFuncSetAttribute(k3_wo, cudaFuncAttributeMaxDynamicSharedMemorySize, K3_SMEM);
        cudaFuncSetAttribute(k4_glu, cudaFuncAttributeMaxDynamicSharedMemorySize, K4_SMEM);
        cudaFuncSetAttribute(k5_down, cudaFuncAttributeMaxDynamicSharedMemorySize, K5_SMEM);
    }
    void *po, *ph, *phh;
    cudaGetSymbolAddress(&po, g_o); cudaGetSymbolAddress(&ph, g_h); cudaGetSymbolAddress(&phh, g_hh);
    const CUtensorMap tmX = make_map(enc, x, DM, SEQ, 64, 128), tmW = make_map(enc, wqkv, NQKV, DM, 64, 64);
    const CUtensorMap tmWo = make_map(enc, wo, DM, DM, 64, 64), tmO = make_map(enc, po, DM, SEQ, 64, 80);
    const CUtensorMap tmXr = make_map(enc, x, DM, SEQ, 64, 80), tmH80 = make_map(enc, ph, DM, SEQ, 64, 80);
    const CUtensorMap tmH = make_map(enc, ph, DM, SEQ, 64, 128);
    const CUtensorMap tmG64 = make_map(enc, wg, FF, DM, 64, 64), tmU64 = make_map(enc, wu, FF, DM, 64, 64);
    const CUtensorMap tmG32 = make_map(enc, wg, FF, DM, 32, 128), tmU32 = make_map(enc, wu, FF, DM, 32, 128);
    const CUtensorMap tmWd = make_map_perm(enc, wd, 4), tmHH = make_map(enc, phh, FF, SEQ, 64, 80);
    const CUtensorMap tmOut = make_map(enc, d_out, DM, SEQ, 64, 80);

    launch(k1_qkv, 128, 288, K1_SMEM, false, tmX, tmW, x, wqkv);
    launch(k2_attn, 132, 384, K2_SMEM, true, wo, wg, wu, wd, 65536u, placed);
    launch(k3_wo, placed ? NSM : 130, 352, K3_SMEM, true, tmWo, tmO, tmXr, tmH80, placed);
    launch(k4_glu, 128, 384, K4_SMEM, true, tmH, tmG64, tmU64, tmG32, tmU32);
    launch(k5_down, placed ? NSM : 130, 352, K5_SMEM, true, tmWd, tmHH, tmH80, tmOut, placed);
}
```
